```python
import torch

def _softmax(x, axis=-1):
    return torch.softmax(x, dim=axis)

def _gelu(x):
    return torch.nn.functional.gelu(x, approximate='tanh')

def _silu(x):
    return torch.nn.functional.silu(x)

def _sigmoid(x):
    return torch.sigmoid(x)

def _layernorm(x, axis=-1, eps=1e-05):
    m = x.mean(dim=axis, keepdim=True)
    v = x.var(dim=axis, keepdim=True, unbiased=False)
    return (x - m) / torch.sqrt(v + eps)

def _scatter_add(tgt, idx, src, axis=0):
    return tgt.clone().index_add_(axis, idx, src)

def _segment_sum(src, seg, n):
    out = torch.zeros((n,) + src.shape[1:], dtype=src.dtype)
    return out.index_add_(0, seg, src)

def _pad(x, pw):
    flat = tuple((v for pair in reversed(pw) for v in pair))
    return torch.nn.functional.pad(x, flat)
kernel_name = 'standalone__factorization_afm__recsys'

def setup_inputs():

    _w = lambda a: (lambda t: t.to(torch.bfloat16) if t.is_floating_point() else t)(torch.as_tensor(a))
    B, F, D, V = (4096, 26, 128, min(1000, 100000))
    A = D
    ii, jj = tuple(torch.triu_indices(F, F, 1).unbind(0))
    return {'idx': _w((lambda lo, hi, *s: torch.randint(lo, hi, s))(0, V, B, F).to(torch.int64)), 'table': _w((lambda *s: torch.randn(*s, dtype=torch.bfloat16) * 0.2)(V, D)), 'ii': _w(ii.to(torch.int64)), 'jj': _w(jj.to(torch.int64)), 'W': _w((lambda *s: torch.randn(*s, dtype=torch.bfloat16) * 1.6)(D, A) * (1.0 / D ** 0.5)), 'b': _w((lambda *s: torch.randn(*s, dtype=torch.bfloat16) * 1.6)(A)), 'h': _w((lambda *s: torch.randn(*s, dtype=torch.bfloat16) * 1.6)(A)), 'p': _w((lambda *s: torch.randn(*s, dtype=torch.bfloat16) * 0.2)(D))}

def reference(idx, table, ii, jj, W, b, h, p):
    emb = table[idx]
    ei = emb[:, ii, :].clone()
    ej = emb[:, jj, :].clone()
    pair = ei * ej
    hid = pair @ W + b
    hid = 0.5 * (hid + torch.abs(hid))
    e = hid @ h
    alpha = _softmax(e, axis=-1)
    pooled = torch.einsum('bp,bpd->bd', alpha, pair)
    return pooled @ p
```

```cpp
#include <cuda_runtime.h>
#include <cuda_bf16.h>
#include <cuda_fp16.h>
#include <stdint.h>

namespace {

constexpr int B_ = 4096, F_ = 26, V_ = 1000, P_ = 325;
constexpr int NOWN = 125, NROUTE = 7, NCTA = NOWN + NROUTE, NTHR = 384;
constexpr int RROWS = 586, SEG = 15360;
constexpr float LOG2E = 1.4426950408889634f;
constexpr int SPIN_LIMIT = 1 << 17;

constexpr int OFF_W = 0;
constexpr int WLBO = 17 * 128;
constexpr int OFF_T = 16 * WLBO;
constexpr int OFF_ES = OFF_T + 131072;
constexpr int OFF_SC = OFF_ES + 36864;
constexpr int OFF_ML = OFF_SC + 4096;
constexpr int OFF_X = OFF_ML + 2944;
constexpr int XCAP = 288, LCAP = 1216;
constexpr int OFF_L = OFF_X + XCAP * 56;
constexpr int OFF_BAR = OFF_L + LCAP * 4;
constexpr int OFF_Q = OFF_BAR + 512;
constexpr int SMEM_BYTES = OFF_Q + 1024;
constexpr int BAR_CONV = 0;
constexpr int BAR_GRP = 16;
constexpr int BAR_SCALE = 19;
constexpr int BAR_STAGE = 20;
constexpr int BAR_RAW = 21;
constexpr int BAR_WRAW = 29, BAR_WDONE = 30;
constexpr int OFF_MISC = OFF_BAR + 32 * 8;

__device__ uint32_t g_epoch;
__device__ uint32_t g_ticket;
__device__ unsigned long long g_desc[NOWN * 32];
__device__ uint4 g_sorted[NROUTE * SEG / 4];
__device__ uint4 g_idx9[B_ * 4];
__device__ uint4 g_part[B_ * 32];

__device__ __forceinline__ uint32_t smem_u32(const void* p) { return (uint32_t)__cvta_generic_to_shared(p); }
__device__ __forceinline__ uint32_t hmul2(uint32_t a, uint32_t b) { uint32_t d; asm("mul.rn.f16x2 %0, %1, %2;" : "=r"(d) : "r"(a), "r"(b)); return d; }
__device__ __forceinline__ uint32_t hadd2(uint32_t a, uint32_t b) { uint32_t d; asm("add.rn.f16x2 %0, %1, %2;" : "=r"(d) : "r"(a), "r"(b)); return d; }
__device__ __forceinline__ uint32_t hfma2(uint32_t a, uint32_t b, uint32_t c) { uint32_t d; asm("fma.rn.f16x2 %0, %1, %2, %3;" : "=r"(d) : "r"(a), "r"(b), "r"(c)); return d; }
__device__ __forceinline__ uint32_t hfma2_relu(uint32_t a, uint32_t b, uint32_t c) { uint32_t d; asm("fma.rn.relu.f16x2 %0, %1, %2, %3;" : "=r"(d) : "r"(a), "r"(b), "r"(c)); return d; }
__device__ __forceinline__ uint32_t bmul2(uint32_t a, uint32_t b) { uint32_t d; asm("mul.rn.bf16x2 %0, %1, %2;" : "=r"(d) : "r"(a), "r"(b)); return d; }
__device__ __forceinline__ uint32_t babsmax2(uint32_t a, uint32_t b) {
    uint32_t d; asm("max.xorsign.abs.bf16x2 %0, %1, %2;" : "=r"(d) : "r"(a), "r"(b)); return d;
}
__device__ __forceinline__ uint32_t bmag(uint32_t m2) { return max(m2 & 0x7fffu, (m2 >> 16) & 0x7fffu); }
__device__ __forceinline__ uint4 ldg128(const void* p) {
    uint4 v; asm volatile("ld.global.nc.v4.u32 {%0,%1,%2,%3}, [%4];" : "=r"(v.x), "=r"(v.y), "=r"(v.z), "=r"(v.w) : "l"(p)); return v;
}
__device__ __forceinline__ uint4 ldcg128(const void* p) {
    uint4 v; asm volatile("ld.global.cg.v4.u32 {%0,%1,%2,%3}, [%4];" : "=r"(v.x), "=r"(v.y), "=r"(v.z), "=r"(v.w) : "l"(p) : "memory"); return v;
}
__device__ __forceinline__ uint4 lds128(uint32_t a) {
    uint4 v; asm volatile("ld.shared.v4.u32 {%0,%1,%2,%3}, [%4];" : "=r"(v.x), "=r"(v.y), "=r"(v.z), "=r"(v.w) : "r"(a) : "memory"); return v;
}
__device__ __forceinline__ uint2 lds64(uint32_t a) {
    uint2 v; asm volatile("ld.shared.v2.u32 {%0,%1}, [%2];" : "=r"(v.x), "=r"(v.y) : "r"(a) : "memory"); return v;
}
__device__ __forceinline__ uint32_t lds32(uint32_t a) { uint32_t v; asm volatile("ld.shared.u32 %0, [%1];" : "=r"(v) : "r"(a) : "memory"); return v; }
__device__ __forceinline__ void sts128(uint32_t a, uint4 v) { asm volatile("st.shared.v4.u32 [%0], {%1,%2,%3,%4};" :: "r"(a), "r"(v.x), "r"(v.y), "r"(v.z), "r"(v.w) : "memory"); }
__device__ __forceinline__ void sts64(uint32_t a, uint32_t x, uint32_t y) { asm volatile("st.shared.v2.u32 [%0], {%1,%2};" :: "r"(a), "r"(x), "r"(y) : "memory"); }
__device__ __forceinline__ void sts32(uint32_t a, uint32_t x) { asm volatile("st.shared.u32 [%0], %1;" :: "r"(a), "r"(x) : "memory"); }
__device__ __forceinline__ float bf_lo(uint32_t x) { return __uint_as_float(x << 16); }
__device__ __forceinline__ float bf_hi(uint32_t x) { return __uint_as_float(x & 0xffff0000u); }
__device__ __forceinline__ uint32_t pack_bf16(float lo, float hi) { uint32_t d; asm("cvt.rn.bf16x2.f32 %0, %1, %2;" : "=r"(d) : "f"(hi), "f"(lo)); return d; }
__device__ __forceinline__ uint32_t pack_f16(float lo, float hi) { uint32_t d; asm("cvt.rn.f16x2.f32 %0, %1, %2;" : "=r"(d) : "f"(hi), "f"(lo)); return d; }
__device__ __forceinline__ uint32_t cvt_scaled(uint32_t x, uint32_t sc) { uint32_t y = bmul2(x, sc); return pack_f16(bf_lo(y), bf_hi(y)); }
__device__ __forceinline__ float pow2f(int e) { return __uint_as_float((uint32_t)(min(max(e, -126), 127) + 127) << 23); }
__device__ __forceinline__ uint32_t pow2bf2(int e) { return (uint32_t)(min(max(e, -126), 127) + 127) * 0x00800080u; }
__device__ __forceinline__ int bexp(uint32_t m) { return (int)(m >> 7) - 126; }

__device__ __forceinline__ void mbar_init(uint32_t a, int n) { asm volatile("mbarrier.init.shared::cta.b64 [%0], %1;" :: "r"(a), "r"(n) : "memory"); }
__device__ __forceinline__ void mbar_arrive(uint32_t a) { asm volatile("mbarrier.arrive.shared::cta.b64 _, [%0];" :: "r"(a) : "memory"); }
__device__ __forceinline__ void mbar_wait(uint32_t a) {
    uint32_t ok;
#pragma unroll 1
    for (int i = 0; i < SPIN_LIMIT; i++) {
        asm volatile("{.reg .pred p; mbarrier.try_wait.parity.shared::cta.b64 p, [%1], 0; selp.u32 %0, 1, 0, p;}" : "=r"(ok) : "r"(a) : "memory");
        if (ok) break;
    }
}
__device__ __forceinline__ void expect_tx(uint32_t bar, int n) { asm volatile("mbarrier.arrive.expect_tx.shared::cta.b64 _, [%0], %1;" :: "r"(bar), "r"(n) : "memory"); }
__device__ __forceinline__ void bulk(uint32_t dst, const void* src, int n, uint32_t bar) {
    asm volatile("cp.async.bulk.shared::cluster.global.mbarrier::complete_tx::bytes [%0], [%1], %2, [%3];" :: "r"(dst), "l"(src), "r"(n), "r"(bar) : "memory");
}
__device__ __forceinline__ void bar_sync(int id, int n) { asm volatile("bar.sync %0, %1;" :: "r"(id), "r"(n) : "memory"); }

#define WG_FENCE()  asm volatile("wgmma.fence.sync.aligned;" ::: "memory")
#define WG_COMMIT() asm volatile("wgmma.commit_group.sync.aligned;" ::: "memory")
#define WG_WAIT0()  asm volatile("wgmma.wait_group.sync.aligned 0;" ::: "memory")

template <int N>
__device__ __forceinline__ void wg_wait(uint32_t (&d)[34]) {
    asm volatile("wgmma.wait_group.sync.aligned %34;" : "+r"(d[0]), "+r"(d[1]), "+r"(d[2]), "+r"(d[3]), "+r"(d[4]), "+r"(d[5]), "+r"(d[6]), "+r"(d[7]), "+r"(d[8]), "+r"(d[9]), "+r"(d[10]), "+r"(d[11]), "+r"(d[12]), "+r"(d[13]), "+r"(d[14]), "+r"(d[15]), "+r"(d[16]), "+r"(d[17]), "+r"(d[18]), "+r"(d[19]), "+r"(d[20]), "+r"(d[21]), "+r"(d[22]), "+r"(d[23]), "+r"(d[24]), "+r"(d[25]), "+r"(d[26]), "+r"(d[27]), "+r"(d[28]), "+r"(d[29]), "+r"(d[30]), "+r"(d[31]), "+r"(d[32]), "+r"(d[33]) : "n"(N) : "memory");
}
template <int SCALE_D>
__device__ __forceinline__ void wgmma_rs(uint32_t (&d)[34], uint32_t a0, uint32_t a1, uint32_t a2, uint32_t a3, uint64_t desc) {
    asm volatile(
        "{\n.reg .pred p;\nsetp.ne.b32 p, %39, 0;\n"
        "wgmma.mma_async.sync.aligned.m64n136k16.f16.f16.f16 "
        "{%0,%1,%2,%3,%4,%5,%6,%7,%8,%9,%10,%11,%12,%13,%14,%15,%16,%17,%18,%19,%20,%21,%22,%23,%24,%25,%26,%27,%28,%29,%30,%31,%32,%33},"
        "{%34,%35,%36,%37}, %38, p, 1, 1, 1;\n}\n"
        : "+r"(d[0]), "+r"(d[1]), "+r"(d[2]), "+r"(d[3]), "+r"(d[4]), "+r"(d[5]), "+r"(d[6]), "+r"(d[7]), "+r"(d[8]), "+r"(d[9]), "+r"(d[10]), "+r"(d[11]), "+r"(d[12]), "+r"(d[13]), "+r"(d[14]), "+r"(d[15]), "+r"(d[16]), "+r"(d[17]), "+r"(d[18]), "+r"(d[19]), "+r"(d[20]), "+r"(d[21]), "+r"(d[22]), "+r"(d[23]), "+r"(d[24]), "+r"(d[25]), "+r"(d[26]), "+r"(d[27]), "+r"(d[28]), "+r"(d[29]), "+r"(d[30]), "+r"(d[31]), "+r"(d[32]), "+r"(d[33])
        : "r"(a0), "r"(a1), "r"(a2), "r"(a3), "l"(desc), "n"(SCALE_D));
}

__device__ __forceinline__ void wgmma_rs0(uint32_t (&d)[34], uint32_t a0, uint32_t a1, uint32_t a2, uint32_t a3, uint64_t desc) {
    asm volatile(
        "{\n.reg .pred p;\nsetp.ne.b32 p, %39, 0;\n"
        "wgmma.mma_async.sync.aligned.m64n136k16.f16.f16.f16 "
        "{%0,%1,%2,%3,%4,%5,%6,%7,%8,%9,%10,%11,%12,%13,%14,%15,%16,%17,%18,%19,%20,%21,%22,%23,%24,%25,%26,%27,%28,%29,%30,%31,%32,%33},"
        "{%34,%35,%36,%37}, %38, p, 1, 1, 1;\n}\n"
        : "=r"(d[0]), "=r"(d[1]), "=r"(d[2]), "=r"(d[3]), "=r"(d[4]), "=r"(d[5]), "=r"(d[6]), "=r"(d[7]), "=r"(d[8]), "=r"(d[9]), "=r"(d[10]), "=r"(d[11]), "=r"(d[12]), "=r"(d[13]), "=r"(d[14]), "=r"(d[15]), "=r"(d[16]), "=r"(d[17]), "=r"(d[18]), "=r"(d[19]), "=r"(d[20]), "=r"(d[21]), "=r"(d[22]), "=r"(d[23]), "=r"(d[24]), "=r"(d[25]), "=r"(d[26]), "=r"(d[27]), "=r"(d[28]), "=r"(d[29]), "=r"(d[30]), "=r"(d[31]), "=r"(d[32]), "=r"(d[33])
        : "r"(a0), "r"(a1), "r"(a2), "r"(a3), "l"(desc), "n"(0));
}

__device__ __forceinline__ int kappa_inv(int k) { return (k & 0x61) | ((k >> 2) & 6) | ((k & 6) << 2); }

__device__ __forceinline__ void st_rec(uint4* p, float m, float l, float a, uint32_t tag) {
    asm volatile("{.reg .b128 t; .reg .b64 x, y; mov.b64 x, {%1, %2}; mov.b64 y, {%3, %4}; mov.b128 t, {x, y}; st.relaxed.gpu.global.b128 [%0], t;}"
                 :: "l"(p), "r"(__float_as_uint(m)), "r"(__float_as_uint(l)), "r"(__float_as_uint(a)), "r"(tag) : "memory");
}
__device__ __forceinline__ uint4 ld_rec(const uint4* p) {
    uint4 v;
    asm volatile("{.reg .b128 t; .reg .b64 x, y; ld.relaxed.gpu.global.b128 t, [%4]; mov.b128 {x, y}, t; mov.b64 {%0, %1}, x; mov.b64 {%2, %3}, y;}"
                 : "=r"(v.x), "=r"(v.y), "=r"(v.z), "=r"(v.w) : "l"(p) : "memory");
    return v;
}
__device__ __forceinline__ uint32_t dp2a_lo8(uint32_t o, uint32_t c) { uint32_t d; asm("dp2a.lo.u32.u32 %0, %1, %2, %3;" : "=r"(d) : "r"(o), "r"(0x0008u), "r"(c)); return d; }
__device__ __forceinline__ uint32_t dp2a_hi8(uint32_t o, uint32_t c) { uint32_t d; asm("dp2a.lo.u32.u32 %0, %1, %2, %3;" : "=r"(d) : "r"(o), "r"(0x0800u), "r"(c)); return d; }

#define TS(k)
__device__ __forceinline__ float ex2(float x) { float y; asm("ex2.approx.ftz.f32 %0, %1;" : "=f"(y) : "f"(x)); return y; }
__device__ __forceinline__ uint32_t ldcg32(const void* p) { uint32_t v; asm volatile("ld.global.cg.u32 %0, [%1];" : "=r"(v) : "l"(p) : "memory"); return v; }
__device__ __forceinline__ uint32_t ld_relaxed32(const void* p) { uint32_t v; asm volatile("ld.relaxed.gpu.global.u32 %0, [%1];" : "=r"(v) : "l"(p) : "memory"); return v; }
__device__ __forceinline__ void warp_arrive(uint32_t bar) { __syncwarp(); if ((threadIdx.x & 31) == 0) mbar_arrive(bar); }

struct Row { uint4 z0, z1, z2; uint32_t z3; };
__device__ __forceinline__ void load_row(Row& w, uint32_t ent) {
    const uint4* row = g_idx9 + (ent >> 8) * 4;
    w.z0 = ldcg128(row); w.z1 = ldcg128(row + 1); w.z2 = ldcg128(row + 2); w.z3 = ldcg32(row + 3);
}
__device__ __forceinline__ void row_slots(const Row& w, int v0, uint32_t ent, bool plain, uint32_t (&o)[13]) {
    const int vl = ent & 7;
    const uint32_t k1 = ((uint32_t)(vl - 9 * v0) & 0xffffu) * 0x10001u;
    const uint32_t k2 = ((uint32_t)(vl - 9 * v0 + 9 * V_) & 0xffffu) * 0x10001u;
    const uint32_t sent = (uint32_t)(511 * 9 + vl) * 0x10001u;
    const uint32_t z[13] = {w.z0.x, w.z0.y, w.z0.z, w.z0.w, w.z1.x, w.z1.y, w.z1.z, w.z1.w, w.z2.x, w.z2.y, w.z2.z, w.z2.w, w.z3};
#pragma unroll
    for (int k = 0; k < 13; k++) o[k] = __viaddmin_u16x2(z[k], k2, __viaddmin_u16x2(z[k], k1, sent));
    const int self = plain ? (int)(ent >> 4) & 15 : -1;
    const uint32_t keep = (ent & 8) ? 0x0000ffffu : 0xffff0000u;
#pragma unroll
    for (int k = 0; k < 13; k++) if (k == self) o[k] = (o[k] & keep) | (sent & ~keep);
}
template <int K0, int N>
__device__ __forceinline__ void lookup_part(const uint32_t (&o)[13], uint32_t sES, uint32_t ml, float& m, float& l, float& a) {
    float e[2 * N], s[2 * N];
#pragma unroll
    for (int k = 0; k < N; k++) {
        const uint2 x = lds64(dp2a_lo8(o[K0 + k], sES)), y = lds64(dp2a_hi8(o[K0 + k], sES));
        e[2 * k] = __uint_as_float(x.x); s[2 * k] = __uint_as_float(x.y);
        e[2 * k + 1] = __uint_as_float(y.x); s[2 * k + 1] = __uint_as_float(y.y);
    }
    if (ml) {
#pragma unroll
        for (int k = 0; k < (N + 1) / 2; k++) {
            uint4 v = lds128(ml + K0 * 8 + 16 * k);
            e[4 * k] += __uint_as_float(v.x); e[4 * k + 1] += __uint_as_float(v.y);
            if (4 * k + 2 < 2 * N) { e[4 * k + 2] += __uint_as_float(v.z); e[4 * k + 3] += __uint_as_float(v.w); }
        }
    }
    float m0 = m, m1 = -INFINITY;
#pragma unroll
    for (int k = 0; k < N; k++) { m0 = fmaxf(m0, e[2 * k]); m1 = fmaxf(m1, e[2 * k + 1]); }
    const float mn = fmaxf(m0, m1);
    const float ms = (mn == -INFINITY) ? 0.f : mn;
    float l0 = 0.f, l1 = 0.f, a0 = 0.f, a1 = 0.f;
    if (K0 > 0) { const float c = ex2(m - ms); l0 = l * c; a0 = a * c; }
#pragma unroll
    for (int k = 0; k < N; k++) {
        const float w0 = ex2(e[2 * k] - ms), w1 = ex2(e[2 * k + 1] - ms);
        l0 += w0; a0 = fmaf(w0, s[2 * k], a0);
        l1 += w1; a1 = fmaf(w1, s[2 * k + 1], a1);
    }
    m = mn; l = l0 + l1; a = a0 + a1;
}
__device__ __noinline__ void lookup_fn(uint32_t o0, uint32_t o1, uint32_t o2, uint32_t o3, uint32_t o4, uint32_t o5, uint32_t o6, uint32_t o7, uint32_t o8,
                                       uint32_t o9, uint32_t o10, uint32_t o11, uint32_t o12, uint32_t sb, uint32_t ent, uint32_t tag, bool plain) {
    const uint32_t o[13] = {o0, o1, o2, o3, o4, o5, o6, o7, o8, o9, o10, o11, o12};
    const uint32_t i = (ent >> 3) & 31, ml = plain ? 0u : sb + OFF_ML + i * 112;
    float m = -INFINITY, l = 0.f, a = 0.f;
    lookup_part<0, 6>(o, sb + OFF_ES, ml, m, l, a);
    lookup_part<6, 7>(o, sb + OFF_ES, ml, m, l, a);
    st_rec(g_part + (ent >> 8) * 32 + i, m, l, a, tag);
}
__device__ __forceinline__ void lookup(const uint32_t (&o)[13], uint32_t sb, uint32_t ent, uint32_t tag, bool plain) {
    lookup_fn(o[0], o[1], o[2], o[3], o[4], o[5], o[6], o[7], o[8], o[9], o[10], o[11], o[12], sb, ent, tag, plain);
}
__device__ __forceinline__ void staged_lookup(uint32_t sb, int x, uint32_t tag, bool plain) {
    uint32_t o[13], ent;
#pragma unroll
    for (int k = 0; k < 7; k++) {
        uint2 v = lds64(sb + OFF_X + (k * XCAP + x) * 8);
        o[2 * k] = v.x; if (k < 6) o[2 * k + 1] = v.y; else ent = v.y;
    }
    lookup(o, sb, ent, tag, plain);
}
__device__ __forceinline__ void combine(__nv_bfloat16* out, uint32_t tag) {
    const int warp = threadIdx.x >> 5, lane = threadIdx.x & 31;
    const int r0 = 3 * warp, b0 = blockIdx.x * 32 + r0;
    if (r0 >= 32) return;
    const bool on = lane < F_, third = r0 + 2 < 32;
    const uint4* p = g_part + b0 * 32 + lane;
    uint4 rec[3];
#pragma unroll
    for (int r = 0; r < 3; r++) rec[r] = make_uint4(0, 0, 0, (on && (r < 2 || third)) ? ~tag : tag);
#pragma unroll 1
    for (int it = 0; it < SPIN_LIMIT; it++) {
#pragma unroll
        for (int r = 0; r < 3; r++) if (rec[r].w != tag) rec[r] = ld_rec(p + 32 * r);
        if (it == 0) TS(28);
        if (__all_sync(0xffffffffu, rec[0].w == tag && rec[1].w == tag && rec[2].w == tag)) break;
        __nanosleep(100);
    }
    TS(29 + (threadIdx.x >> 7));
    float l[3], a[3];
#pragma unroll
    for (int r = 0; r < 3; r++) {
        const float m = on ? __uint_as_float(rec[r].x) : -INFINITY;
        int key = __float_as_int(m); key ^= (key >> 31) & 0x7fffffff;
        key = __reduce_max_sync(0xffffffffu, key); key ^= (key >> 31) & 0x7fffffff;
        const float c = ex2(m - __int_as_float(key));
        l[r] = __uint_as_float(rec[r].y) * c; a[r] = __uint_as_float(rec[r].z) * c;
    }
#pragma unroll
    for (int o = 16; o; o >>= 1)
#pragma unroll
        for (int r = 0; r < 3; r++) { l[r] += __shfl_xor_sync(0xffffffffu, l[r], o); a[r] += __shfl_xor_sync(0xffffffffu, a[r], o); }
    if (lane < 2 || (lane == 2 && third)) {
        const float ll = lane == 0 ? l[0] : lane == 1 ? l[1] : l[2], aa = lane == 0 ? a[0] : lane == 1 ? a[1] : a[2];
        out[b0 + lane] = __float2bfloat16(__fdividef(aa, ll));
    }
}
__device__ __forceinline__ void finish() {
    if (atomicAdd(&g_ticket, 1u) == NCTA - 1) { g_ticket = 0; atomicAdd(&g_epoch, 1u); }
}

struct Tile { uint32_t rr0, rr1; float mul; int pos; };

struct Mma {
    uint32_t bb[16], hh[16], f0[16], f1[16], cu[16], a[32];
    uint32_t rv0, rv1, sb, pu, sx, sy;
    uint4 px; uint32_t ps; float pm; int pp;
    float cv, ce, cs;
    int pos, vp, tsw;
    uint64_t desc;

    __device__ __forceinline__ void set_v(int slab) {
        const int q = threadIdx.x & 3, g = (threadIdx.x >> 2) & 7;
        const uint32_t p = sb + OFF_T + vp * 512 + q * 16;
#pragma unroll
        for (int m = 0; m < 4; m++) {
            uint4 x = lds128(p + m * 64), y = lds128(p + 256 + (m ^ 1) * 64);
            f0[4 * m] = x.x; f0[4 * m + 1] = x.y; f0[4 * m + 2] = x.z; f0[4 * m + 3] = x.w;
            f1[4 * m] = y.x; f1[4 * m + 1] = y.y; f1[4 * m + 2] = y.z; f1[4 * m + 3] = y.w;
        }
        const uint4 s = lds128(sb + OFF_SC + vp * 16);
        rv0 = s.x; rv1 = s.z; cv = __uint_as_float((q & 1) ? s.w : s.y);
        const int r = 8 * slab + 2 * vp + g;
        pu = sb + OFF_T + r * 256 + q * 16 + (g & 1) * 64;
        pos = (8 * slab + g - (q & 1)) * 65536 + r * 72 + (2 * vp + (q & 1)) * 8;
    }
    __device__ __forceinline__ void load_u() {
        const uint32_t p1 = pu ^ 64;
        uint4 x = lds128(pu), y = lds128(p1), z = lds128(pu + 128), v = lds128(p1 + 128);
        cu[0] = x.x; cu[1] = x.y; cu[2] = x.z; cu[3] = x.w; cu[4] = y.x; cu[5] = y.y; cu[6] = y.z; cu[7] = y.w;
        cu[8] = z.x; cu[9] = z.y; cu[10] = z.z; cu[11] = z.w; cu[12] = v.x; cu[13] = v.y; cu[14] = v.z; cu[15] = v.w;
        const uint2 s = lds64((((pu - sb - OFF_T) >> 8) << 3) + sb + OFF_SC);
        sx = s.x; sy = s.y;
    }
    __device__ __forceinline__ void issue(uint32_t (&acc)[34], uint32_t (&old)[34], Tile& n, int tn) {
#pragma unroll
        for (int k = 0; k < 16; k++) { a[2 * k] = hmul2(cu[k], f0[k]); a[2 * k + 1] = hmul2(cu[k], f1[k]); }
        WG_FENCE();
        wgmma_rs0(acc, a[0], a[1], a[2], a[3], desc);
#pragma unroll
        for (int s = 1; s < 8; s++) wgmma_rs<1>(acc, a[4 * s], a[4 * s + 1], a[4 * s + 2], a[4 * s + 3], desc + (uint64_t)(s * (2 * WLBO >> 4)));
        WG_COMMIT();
        wg_wait<1>(old);
        n.rr0 = hmul2(sx, rv0); n.rr1 = hmul2(sx, rv1); n.mul = __uint_as_float(sy) * cv; n.pos = pos;
        pu += 32 * 256; pos += 32 * 65536 + 32 * 72;
        if (tn == tsw) {
            const int wg = threadIdx.x >> 7, w = (threadIdx.x >> 5) & 3, k = 4 * tn + w, first = vp < 2;
            vp = first ? 2 : 3; tsw = (wg && w) ? 23 : 24; if (!first) tsw = -1;
            set_v(k - (first ? (wg ? 30 : 63) : (wg ? 61 : 96))); TS(wg * 8 + (first ? 3 : 4));
        }
        if (tn < 15) mbar_wait(sb + OFF_BAR + (BAR_CONV + tn + 1) * 8);
    }
    __device__ __forceinline__ void flush(int t) {
        const uint32_t x = hadd2(hadd2(px.x, px.y), hadd2(px.z, px.w));
        const uint32_t y = __byte_perm(x, ps, (threadIdx.x & 1) ? 0x7632 : 0x5410);
        const __half2 h2 = *reinterpret_cast<const __half2*>(&y);
        float e = __low2float(h2) * ce * pm;
        const float s = __high2float(h2) * cs * pm;
        const uint32_t d = (uint32_t)pp >> 16;
        e -= (d == 0 || d == 500) ? 1.f : 0.f;
        e = d > 500u ? -INFINITY : e;
        sts64(sb + OFF_ES + (pp & 0xffff), __float_as_uint(e), __float_as_uint(s));
        asm volatile("{.reg .pred p; setp.eq.s32 p, %1, 15; setp.eq.or.s32 p, %1, 23, p; @p mbarrier.arrive.shared::cta.b64 _, [%0];}"
                     :: "r"(sb + OFF_BAR + BAR_GRP * 8 + (t & 16) / 2), "r"(t) : "memory");
    }
    template <bool NEXT>
    __device__ __forceinline__ void epilogue(const uint32_t (&acc)[34], const Tile& c, int t) {
        flush(t - 1);
        uint32_t e0 = 0, e1 = 0, e2 = 0, e3 = 0;
#pragma unroll
        for (int j = 0; j < 16; j += 2) {
            e0 = hfma2(hfma2_relu(bb[j], c.rr0, acc[2 * j]), hh[j], e0);
            e1 = hfma2(hfma2_relu(bb[j], c.rr1, acc[2 * j + 1]), hh[j], e1);
            e2 = hfma2(hfma2_relu(bb[j + 1], c.rr0, acc[2 * j + 2]), hh[j + 1], e2);
            e3 = hfma2(hfma2_relu(bb[j + 1], c.rr1, acc[2 * j + 3]), hh[j + 1], e3);
            if (j == 4 && NEXT) load_u();
        }
        e0 = hadd2(e0, e2); e1 = hadd2(e1, e3);
        sts32(sb + OFF_Q + threadIdx.x * 4, hadd2(__byte_perm(e0, e1, 0x5410), __byte_perm(e0, e1, 0x7632)));
        __syncwarp();
        px = lds128(sb + OFF_Q + (threadIdx.x & ~3) * 4);
        ps = __byte_perm(acc[32], acc[33], 0x5410);
        pm = c.mul; pp = c.pos;
    }
};

__device__ __forceinline__ void fetch_raw(uint32_t sb, const uint8_t* table, int v0, int r0) {
    const int lane = threadIdx.x & 31;
    if (r0 < 512) {
#pragma unroll 1
        for (int k = 0; k < 4; k++) {
            const int r = r0 + 8 * k, u = v0 + r - (v0 + r >= V_ ? V_ : 0);
#pragma unroll
            for (int z = 0; z < 4; z++)
                asm volatile("cp.async.cg.shared.global [%0], [%1], 16;" :: "r"(sb + OFF_T + r * 256 + lane * 16 + z * 512), "l"(table + u * 256 + lane * 16 + z * 512) : "memory");
        }
    }
    asm volatile("cp.async.commit_group;" ::: "memory");
}
__device__ __forceinline__ uint32_t row_max(uint32_t sb, int r) {
    const uint32_t p = sb + OFF_T + r * 256;
    uint32_t m0 = 0, m1 = 0;
#pragma unroll 8
    for (int k = 0; k < 16; k++) {
        const uint4 x = lds128(p + (((k + r) & 15) << 4));
        m0 = babsmax2(m0, babsmax2(x.x, x.y)); m1 = babsmax2(m1, babsmax2(x.z, x.w));
    }
    return babsmax2(m0, m1);
}
__device__ __forceinline__ void convert_row(uint32_t sb, int r, uint32_t mx, int amin) {
    const uint32_t p = sb + OFF_T + r * 256;
    const int a = min(max(bexp(bmag(mx)), amin), 126);
    const uint32_t sc = pow2bf2(-a), sw = (r & 1) << 6;
    const float rho = pow2f(amin - a);
    sts64(sb + OFF_SC + r * 8, pack_f16(rho, rho), __float_as_uint(pow2f(a)));
#pragma unroll 1
    for (int hf = 0; hf < 2; hf++) {
        uint4 x[8];
#pragma unroll
        for (int k = 0; k < 8; k++) x[k] = lds128(p + hf * 128 + (((k + r) & 7) << 4));
#pragma unroll
        for (int k = 0; k < 8; k++)
            sts128(p + hf * 128 + ((((k + r) & 7) << 4) ^ sw), make_uint4(cvt_scaled(x[k].x, sc), cvt_scaled(x[k].y, sc), cvt_scaled(x[k].z, sc), cvt_scaled(x[k].w, sc)));
    }
}
__device__ __forceinline__ uint32_t fetch_entry(int n, int limit, int pre, int base) {
    int lo = 0;
#pragma unroll
    for (int s = 16; s; s >>= 1) { const int pc = __shfl_sync(0xffffffffu, pre, lo + s); if (pc <= n) lo += s; }
    const int bs = __shfl_sync(0xffffffffu, base, lo);
    return n < limit ? ldcg32((const uint32_t*)g_sorted + bs + n) : 0u;
}

__device__ __forceinline__ void router(const int* __restrict__ idx, uint8_t* smem, uint32_t tag) {
    const int tid = threadIdx.x, rt = blockIdx.x - NOWN;
    const int row0 = rt * RROWS, n4 = (min(B_, row0 + RROWS) - row0) * F_ / 4;
    uint32_t* hist = (uint32_t*)smem;
    uint32_t* wsum = hist + 384;
    uint32_t* sorted = (uint32_t*)(smem + 2048);
    uint32_t v[40], en[40];
#pragma unroll
    for (int k = 0; k < 10; k++) {
        uint4 x = make_uint4(0, 0, 0, 0);
        if (tid + k * NTHR < n4) x = ldg128(idx + row0 * F_ + (tid + k * NTHR) * 4);
        v[4 * k] = x.x; v[4 * k + 1] = x.y; v[4 * k + 2] = x.z; v[4 * k + 3] = x.w;
    }
    hist[tid] = 0;
    __syncthreads(); TS(2);
#pragma unroll
    for (int k = 0; k < 40; k += 2) {
        const int x = (tid + (k >> 2) * NTHR) * 2 + ((k >> 1) & 1);
        if (x < 2 * n4) {
            const uint32_t rw = row0 + x / 13, i2 = x % 13;
            const uint32_t u0 = min(v[k], (uint32_t)(V_ - 1)), u1 = min(v[k + 1], (uint32_t)(V_ - 1));
            ((uint32_t*)g_idx9)[rw * 16 + i2] = (u0 | u1 << 16) * 9;
            const uint32_t k0 = (u0 >> 3) * 3 + max(((int)(u0 >> 1) & 3) - 1, 0), k1 = (u1 >> 3) * 3 + max(((int)(u1 >> 1) & 3) - 1, 0);
            en[k] = rw << 8 | i2 << 4 | (u0 & 7); en[k + 1] = rw << 8 | i2 << 4 | 8 | (u1 & 7);
            v[k] = k0 << 16 | atomicAdd(&hist[k0], 1u); v[k + 1] = k1 << 16 | atomicAdd(&hist[k1], 1u);
        }
    }
    __syncthreads();
    const uint32_t cnt = hist[tid]; TS(3);
    uint32_t inc = cnt;
#pragma unroll
    for (int o = 1; o < 32; o <<= 1) { const uint32_t y = __shfl_up_sync(0xffffffffu, inc, o); if ((tid & 31) >= o) inc += y; }
    if ((tid & 31) == 31) wsum[tid >> 5] = inc;
    __syncthreads();
    uint32_t start = inc - cnt;
    for (int k = 0; k < (tid >> 5); k++) start += wsum[k];
    hist[tid] = start;
    __syncthreads();
#pragma unroll
    for (int k = 0; k < 40; k++)
        if (tid + (k >> 2) * NTHR < n4) sorted[hist[v[k] >> 16] + (v[k] & 0xffffu)] = en[k];
    __syncthreads();
    for (int c = tid; c < n4; c += NTHR) g_sorted[rt * (SEG / 4) + c] = ((const uint4*)sorted)[c];
    __syncthreads();
    if (tid < NOWN * 3) {
        __threadfence();
        asm volatile("st.relaxed.gpu.global.u64 [%0], %1;" :: "l"(g_desc + (tid / 3) * 32 + (tid % 3) * NROUTE + rt),
                     "l"((unsigned long long)tag << 32 | cnt << 16 | start) : "memory");
    }
}

__global__ void __launch_bounds__(NTHR, 1)
afm_kernel(const int* __restrict__ idx, const uint8_t* __restrict__ table, const int* __restrict__ ii, const int* __restrict__ jj,
           const uint8_t* __restrict__ W, const uint8_t* __restrict__ bias, const uint8_t* __restrict__ hvec,
           const uint8_t* __restrict__ pvec, __nv_bfloat16* __restrict__ out) {
    extern __shared__ __align__(1024) uint8_t smem[];
    const uint32_t sb = smem_u32(smem);
    const int tid = threadIdx.x, lane = tid & 31, g = lane >> 2, q = lane & 3;
    if (blockIdx.x >= NOWN) {
        TS(0); const uint32_t tag = ld_relaxed32(&g_epoch) + 1;
        router(idx, smem, tag); TS(1);
        if (blockIdx.x < B_ / 32) combine(out, tag); TS(4);
        __syncthreads();
        if (tid == 0) finish();
        return;
    }
    const int v0 = blockIdx.x * 8;
    if (tid < 256) {
#pragma unroll
        for (int k = 0; k < 8; k++) asm volatile("cp.async.cg.shared.global [%0], [%1], 16;" :: "r"(sb + OFF_ES + tid * 16 + k * 4096), "l"(W + tid * 16 + k * 4096) : "memory");
        const uint8_t* src = tid < 16 ? bias : tid < 32 ? hvec : pvec;
        if (tid < 48) asm volatile("cp.async.cg.shared.global [%0], [%1], 16;" :: "r"(sb + OFF_ES + 32768 + tid * 16), "l"(src + (tid & 15) * 16) : "memory");
    }
    if (tid < 256) {
        asm volatile("setmaxnreg.inc.sync.aligned.u32 208;");
        Mma c;
        const int wg = tid >> 7, w = (tid >> 5) & 3;
        c.sb = sb;
        asm volatile("cp.async.wait_all;" ::: "memory");
        bar_sync(0, 384);
        TS(wg * 8 + 2);
        const uint32_t ch = ((tid >> 3) + tid) & 15, pw = sb + OFF_ES + kappa_inv((tid & 7) | wg << 3) * 256 + ch * 16;
        const uint2 b4 = lds64(sb + OFF_ES + 32768 + lane * 8), h4 = lds64(sb + OFF_ES + 33024 + lane * 8), p4 = lds64(sb + OFF_ES + 33280 + lane * 8);
        const uint32_t pv = lds32(sb + OFF_ES + 33280 + (kappa_inv(tid & 127) >> 1) * 4);
        uint32_t mw = 0;
#pragma unroll 1
        for (int k = 0; k < 2; k++) {
#pragma unroll
            for (int z = 0; z < 4; z++) { const uint4 x = lds128(sb + OFF_ES + tid * 16 + (4 * k + z) * 4096); mw = babsmax2(mw, babsmax2(babsmax2(x.x, x.y), babsmax2(x.z, x.w))); }
        }
        mw = __reduce_max_sync(0xffffffffu, bmag(mw));
        if (lane == 0) sts32(sb + OFF_MISC + (tid >> 5) * 4, mw);
        const uint32_t mb = __reduce_max_sync(0xffffffffu, bmag(babsmax2(b4.x, b4.y)));
        const uint32_t mh = __reduce_max_sync(0xffffffffu, bmag(babsmax2(h4.x, h4.y)));
        const uint32_t mp = __reduce_max_sync(0xffffffffu, bmag(babsmax2(p4.x, p4.y)));
        bar_sync(1, 256);
        mw = __reduce_max_sync(0xffffffffu, lds32(sb + OFF_MISC + (lane & 7) * 4));
        const int ew = max(bexp(mw) - 7, -100), ed = max(bexp(mh) + 7, -100), ep = max(bexp(mp) - 8, -100);
        const int amin = min(max((bexp(mb) - 13 - ew) >> 1, -60), 126);
        if (tid == 0) { sts32(sb + OFF_MISC + 32, (uint32_t)amin); mbar_arrive(sb + OFF_BAR + BAR_SCALE * 8); }
        const uint32_t sw = pow2bf2(-ew);
#pragma unroll 1
        for (int k = 0; k < 4; k++) {
#pragma unroll
            for (int z = 0; z < 2; z++) {
                const uint4 x = lds128(pw + k * 8192 + z * 1024);
                sts128(sb + OFF_W + (4 * k + 2 * z + wg) * WLBO + ch * 128 + (tid & 7) * 16,
                       make_uint4(cvt_scaled(x.x, sw), cvt_scaled(x.y, sw), cvt_scaled(x.z, sw), cvt_scaled(x.w, sw)));
            }
        }
        if (tid < 128) {
            const uint32_t y = __byte_perm(cvt_scaled(pv, pow2bf2(-ep)), 0, (tid & 1) ? 0x3232 : 0x1010);
            sts128(sb + OFF_W + (tid >> 3) * WLBO + 2048 + (tid & 7) * 16, make_uint4(y, y, y, y));
        } else if (tid < 160) {
            const int eb = -2 * amin - ew;
            const float s1 = pow2f(eb >> 1), s2 = pow2f(eb - (eb >> 1));
            const uint32_t sh = pow2bf2(-ed), dst = sb + OFF_L + (lane & 1) * 128 + (lane >> 1) * 4;
            sts32(dst, pack_f16(bf_lo(b4.x) * s1 * s2, bf_hi(b4.x) * s1 * s2)); sts32(dst + 64, pack_f16(bf_lo(b4.y) * s1 * s2, bf_hi(b4.y) * s1 * s2));
            sts32(dst + 256, cvt_scaled(h4.x, sh)); sts32(dst + 320, cvt_scaled(h4.y, sh));
        }
        asm volatile("fence.proxy.async.shared::cta;" ::: "memory");
        c.ce = pow2f(ew + ed) * LOG2E; c.cs = pow2f(ep);
        c.desc = (uint64_t)(((sb + OFF_W) & 0x3FFFF) >> 4) | ((uint64_t)(WLBO >> 4) << 16) | ((uint64_t)(128 >> 4) << 32);
        c.vp = wg; c.tsw = w == 3 ? 15 : 16;
        c.px = make_uint4(0, 0, 0, 0); c.ps = 0; c.pm = 0.f; c.pp = 64;
        bar_sync(1, 256);
#pragma unroll
        for (int m = 0; m < 4; m++) {
            const uint4 x = lds128(sb + OFF_L + q * 64 + m * 16), y = lds128(sb + OFF_L + 256 + q * 64 + m * 16);
            c.bb[4 * m] = x.x; c.bb[4 * m + 1] = x.y; c.bb[4 * m + 2] = x.z; c.bb[4 * m + 3] = x.w;
            c.hh[4 * m] = y.x; c.hh[4 * m + 1] = y.y; c.hh[4 * m + 2] = y.z; c.hh[4 * m + 3] = y.w;
        }
        warp_arrive(sb + OFF_BAR + BAR_WDONE * 8);
        TS(wg * 8 + 1);
#pragma unroll 1
        for (int k = 0; k < 2; k++) mbar_wait(sb + OFF_BAR + (BAR_CONV + k) * 8);
        c.set_v(w); c.load_u(); TS(wg * 8);
        uint32_t acc0[34], acc1[34];
        Tile t0, t1;
        c.issue(acc0, acc0, t0, 1); c.load_u();
#pragma unroll 1
        for (int t = 0; t < 30; t += 2) {
            WG_WAIT0(); c.issue(acc1, acc0, t1, t + 2); c.epilogue<true>(acc0, t0, t);
            WG_WAIT0(); c.issue(acc0, acc1, t0, t + 3); c.epilogue<true>(acc1, t1, t + 1);
        }
        WG_WAIT0();
        if (wg == 0) {
            c.issue(acc1, acc0, t1, 32); c.epilogue<false>(acc0, t0, 30);
            wg_wait<0>(acc1); c.epilogue<false>(acc1, t1, 31); c.flush(0);
        } else {
            wg_wait<0>(acc0); c.epilogue<false>(acc0, t0, 30); c.flush(0);
        }
        warp_arrive(sb + OFF_BAR + (BAR_GRP + 2) * 8); TS(wg * 8 + 5);
        asm volatile("setmaxnreg.dec.sync.aligned.u32 88;");
    } else {
        asm volatile("setmaxnreg.dec.sync.aligned.u32 88;");
        const int ht = tid - 256, hw = ht >> 5;
        fetch_raw(sb, table, v0, 32 * hw);
        if (ht < 31) mbar_init(sb + OFF_BAR + ht * 8, (ht == BAR_GRP + 2 || ht == BAR_WDONE) ? 8 : (ht == BAR_GRP || ht == BAR_GRP + 1) ? 256 : ht == BAR_STAGE ? 4 : 1);
        asm volatile("bar.arrive 0, 384;" ::: "memory");
        bar_sync(2, 128); TS(24);
        int amin = 0;
#pragma unroll 1
        for (int j = 0; j < 4; j++) {
            fetch_raw(sb, table, v0, 128 * j + 128 + 32 * hw);
            asm volatile("cp.async.wait_group 1;" ::: "memory");
            __syncwarp();
            const uint32_t mx = row_max(sb, 128 * j + ht);
            if (j == 0) { mbar_wait(sb + OFF_BAR + BAR_SCALE * 8); amin = (int)lds32(sb + OFF_MISC + 32); TS(16); }
            convert_row(sb, 128 * j + ht, mx, amin);
            warp_arrive(sb + OFF_BAR + (BAR_CONV + 4 * j + hw) * 8);
        }
        uint32_t* ml = (uint32_t*)(smem + OFF_ML); TS(17);
        const uint32_t tag = ld_relaxed32(&g_epoch) + 1;
        int pi[3], pj[3];
#pragma unroll
        for (int k = 0; k < 3; k++) { pi[k] = __ldg(ii + min(ht + 128 * k, P_ - 1)); pj[k] = __ldg(jj + min(ht + 128 * k, P_ - 1)); }
        mbar_wait(sb + OFF_BAR + BAR_WDONE * 8);
#pragma unroll 1
        for (int k = ht; k < F_ * 28; k += 128) ml[k] = 0;
        if (ht < 64) {
            const int vl = ht & 7, x = ht >> 3, r = x < (vl & 6) ? x : x + 504;
            sts64(sb + OFF_ES + r * 72 + vl * 8, 0xff800000u, 0u);
        }
        bar_sync(2, 128);
#pragma unroll
        for (int k = 0; k < 3; k++)
            if (ht + 128 * k < P_) { atomicAdd(&ml[pi[k] * 28 + pj[k]], 1u); atomicAdd(&ml[pj[k] * 28 + pi[k]], 1u); }
        bar_sync(2, 128);
        int odd = 0;
#pragma unroll 1
        for (int k = ht; k < F_ * 28; k += 128) {
            const uint32_t c = ml[k];
            odd |= (k % 28 < F_) && c != (k % 29 != 0);
            ml[k] = __float_as_uint(__log2f((float)c));
        }
        asm volatile("{.reg .pred p; setp.ne.s32 p, %0, 0; barrier.red.or.pred p, 2, 128, p; selp.s32 %0, 1, 0, p;}" : "+r"(odd) :: "memory");
        const bool plain = !odd;
        unsigned long long ds = 0;
#pragma unroll 1
        for (int it = 0; it < SPIN_LIMIT; it++) {
            if (lane < 21) asm volatile("ld.acquire.gpu.global.u64 %0, [%1];" : "=l"(ds) : "l"(g_desc + blockIdx.x * 32 + lane) : "memory");
            if (__all_sync(0xffffffffu, lane >= 21 || (uint32_t)(ds >> 32) == tag)) break;
            __nanosleep(100);
        }
        const int cnt = (uint32_t)(ds >> 32) == tag ? (int)((ds >> 16) & 0xffff) : 0; TS(18);
        int inc = cnt;
#pragma unroll
        for (int o = 1; o < 32; o <<= 1) { const int y = __shfl_up_sync(0xffffffffu, inc, o); if (lane >= o) inc += y; }
        const int nA = __shfl_sync(0xffffffffu, inc, 6), nAB = __shfl_sync(0xffffffffu, inc, 13), nT = __shfl_sync(0xffffffffu, inc, 20);
        const int base = (lane % NROUTE) * SEG + (int)(ds & 0xffff) - (inc - cnt);
        const int pre = lane < 21 ? inc - cnt : 0x3fffffff;
        const int nst = max(min(min(nT, LCAP) - nAB, XCAP), 0), nl = min(nAB, LCAP);
        {
            int sp[6], sn[6], sbs[6];
            uint32_t en[6][2];
#pragma unroll
            for (int k = 0; k < 6; k++) {
                const int sg = (20 - hw - 4 * k) & 31;
                sp[k] = __shfl_sync(0xffffffffu, pre, sg) + lane; sn[k] = min(__shfl_sync(0xffffffffu, inc, sg), LCAP);
                sbs[k] = __shfl_sync(0xffffffffu, base, sg);
            }
#pragma unroll
            for (int k = 0; k < 6; k++)
#pragma unroll
                for (int z = 0; z < 2; z++) if (sp[k] + 32 * z < sn[k]) en[k][z] = ldcg32((const uint32_t*)g_sorted + sbs[k] + sp[k] + 32 * z);
#pragma unroll
            for (int k = 0; k < 6; k++) {
#pragma unroll
                for (int z = 0; z < 2; z++) if (sp[k] + 32 * z < sn[k]) sts32(sb + OFF_L + (sp[k] + 32 * z) * 4, en[k][z]);
#pragma unroll 1
                for (int n = sp[k] + 64; n < sn[k]; n += 32) sts32(sb + OFF_L + n * 4, ldcg32((const uint32_t*)g_sorted + sbs[k] + n));
            }
        }
        bar_sync(2, 128);
        uint32_t o[13];
        Row w;
        {
            uint32_t en[3];
#pragma unroll
            for (int k = 0; k < 3; k++) en[k] = ht + 128 * k < nst ? lds32(sb + OFF_L + (nAB + ht + 128 * k) * 4) : 0u;
#pragma unroll
            for (int k = 0; k < 3; k++) {
                if (ht + 128 * k < nst) {
                    load_row(w, en[k]); row_slots(w, v0, en[k], plain, o);
#pragma unroll
                    for (int z = 0; z < 7; z++) sts64(sb + OFF_X + (z * XCAP + ht + 128 * k) * 8, o[2 * z], z < 6 ? o[2 * z + 1] : en[k]);
                }
            }
        }
        if (ht == 0) sts64(sb + OFF_MISC + 40, tag, (uint32_t)nst | (uint32_t)odd << 16);
        uint32_t e1 = ht < nl ? lds32(sb + OFF_L + ht * 4) : 0u, e2 = ht + 128 < nl ? lds32(sb + OFF_L + (ht + 128) * 4) : 0u;
        load_row(w, e1);
        bar_sync(2, 128);
        if (lane == 0) mbar_arrive(sb + OFF_BAR + BAR_STAGE * 8); TS(19);
#pragma unroll 1
        for (int n = ht; n - lane < nl; n += 128) {
            const uint32_t e0 = e1;
            row_slots(w, v0, e0, plain, o);
            e1 = e2; load_row(w, e1);
            e2 = n + 256 < nl ? lds32(sb + OFF_L + (n + 256) * 4) : 0u;
            mbar_wait(sb + OFF_BAR + BAR_GRP * 8); TS((n < 128 ? 20 : 24 + min(n >> 7, 3)));
            if (n - lane + 31 >= nA) mbar_wait(sb + OFF_BAR + (BAR_GRP + 1) * 8);
            if (n < nl) lookup(o, sb, e0, tag, plain);
            __syncwarp();
        }
        TS(21);
#pragma unroll 1
        for (int n = (nAB > LCAP ? LCAP : nAB + nst) + ht; n - lane < nT; n += 128) {
            const uint32_t e0 = fetch_entry(n, nT, pre, base);
            mbar_wait(sb + OFF_BAR + (BAR_GRP + 2) * 8);
            if (n < nT) { load_row(w, e0); row_slots(w, v0, e0, plain, o); lookup(o, sb, e0, tag, plain); }
            __syncwarp();
        }
    }
    mbar_wait(sb + OFF_BAR + BAR_STAGE * 8);
    const uint2 ms = lds64(sb + OFF_MISC + 40);
    mbar_wait(sb + OFF_BAR + (BAR_GRP + 2) * 8);
    if (tid < (int)(ms.y & 0xffffu)) staged_lookup(sb, tid, ms.x, ms.y < 0x10000u);
    __syncwarp(); TS((tid >> 7) * 8 + 6);
    combine(out, ms.x); TS((tid >> 7) * 8 + 7);
    if (tid == 0) finish();
}

}

extern "C" void kernel_launch(void* const* d_in, const int* in_sizes, int n_in, void* d_out, int out_size) {
    static bool configured = false;
    if (!configured) {
        cudaFuncSetAttribute(afm_kernel, cudaFuncAttributeMaxDynamicSharedMemorySize, SMEM_BYTES);
        configured = true;
    }
    afm_kernel<<<NCTA, NTHR, SMEM_BYTES>>>((const int*)d_in[0], (const uint8_t*)d_in[1], (const int*)d_in[2], (const int*)d_in[3],
                                           (const uint8_t*)d_in[4], (const uint8_t*)d_in[5], (const uint8_t*)d_in[6],
                                           (const uint8_t*)d_in[7], (__nv_bfloat16*)d_out);
}
```

```cpp
#include <cuda_runtime.h>
#include <cuda_bf16.h>
#include <cuda_fp16.h>
#include <stdint.h>

namespace {

constexpr int B_ = 4096, F_ = 26, V_ = 1000, P_ = 325;
constexpr int NOWN = 125, NROUTE = 7, NCTA = NOWN + NROUTE, NTHR = 384;
constexpr int RROWS = 586, SEG = 15360;
constexpr float LOG2E = 1.4426950408889634f;
constexpr int SPIN_LIMIT = 1 << 17;

constexpr int OFF_W = 0;
constexpr int WLBO = 17 * 128;
constexpr int OFF_T = 16 * WLBO;
constexpr int OFF_ES = OFF_T + 131072;
constexpr int OFF_SC = OFF_ES + 36864;
constexpr int OFF_ML = OFF_SC + 4096;
constexpr int OFF_X = OFF_ML + 2944;
constexpr int XCAP = 288, LCAP = 1216;
constexpr int OFF_L = OFF_X + XCAP * 56;
constexpr int OFF_BAR = OFF_L + LCAP * 4;
constexpr int OFF_Q = OFF_BAR + 512;
constexpr int SMEM_BYTES = OFF_Q + 1024;
constexpr int BAR_CONV = 0;
constexpr int BAR_GRP = 16;
constexpr int BAR_SCALE = 19;
constexpr int BAR_STAGE = 20;
constexpr int BAR_RAW = 21;
constexpr int BAR_WRAW = 29, BAR_WDONE = 30;
constexpr int OFF_MISC = OFF_BAR + 32 * 8;

__device__ uint32_t g_epoch;
__device__ uint32_t g_done;
__device__ unsigned long long g_desc[NOWN * 32];
__device__ uint4 g_sorted[NROUTE * SEG / 4];
__device__ uint4 g_idx9[B_ * 4];
__device__ uint4 g_part[B_ * 32];

__device__ __forceinline__ uint32_t smem_u32(const void* p) { return (uint32_t)__cvta_generic_to_shared(p); }
__device__ __forceinline__ uint32_t hmul2(uint32_t a, uint32_t b) { uint32_t d; asm("mul.rn.f16x2 %0, %1, %2;" : "=r"(d) : "r"(a), "r"(b)); return d; }
__device__ __forceinline__ uint32_t hadd2(uint32_t a, uint32_t b) { uint32_t d; asm("add.rn.f16x2 %0, %1, %2;" : "=r"(d) : "r"(a), "r"(b)); return d; }
__device__ __forceinline__ uint32_t hfma2(uint32_t a, uint32_t b, uint32_t c) { uint32_t d; asm("fma.rn.f16x2 %0, %1, %2, %3;" : "=r"(d) : "r"(a), "r"(b), "r"(c)); return d; }
__device__ __forceinline__ uint32_t hfma2_relu(uint32_t a, uint32_t b, uint32_t c) { uint32_t d; asm("fma.rn.relu.f16x2 %0, %1, %2, %3;" : "=r"(d) : "r"(a), "r"(b), "r"(c)); return d; }
__device__ __forceinline__ uint32_t bmul2(uint32_t a, uint32_t b) { uint32_t d; asm("mul.rn.bf16x2 %0, %1, %2;" : "=r"(d) : "r"(a), "r"(b)); return d; }
__device__ __forceinline__ uint32_t babsmax2(uint32_t a, uint32_t b) {
    uint32_t d; asm("max.xorsign.abs.bf16x2 %0, %1, %2;" : "=r"(d) : "r"(a), "r"(b)); return d;
}
__device__ __forceinline__ uint32_t bmag(uint32_t m2) { return max(m2 & 0x7fffu, (m2 >> 16) & 0x7fffu); }
__device__ __forceinline__ uint4 ldg128(const void* p) {
    uint4 v; asm volatile("ld.global.nc.v4.u32 {%0,%1,%2,%3}, [%4];" : "=r"(v.x), "=r"(v.y), "=r"(v.z), "=r"(v.w) : "l"(p)); return v;
}
__device__ __forceinline__ uint4 ldcg128(const void* p) {
    uint4 v; asm volatile("ld.global.cg.v4.u32 {%0,%1,%2,%3}, [%4];" : "=r"(v.x), "=r"(v.y), "=r"(v.z), "=r"(v.w) : "l"(p) : "memory"); return v;
}
__device__ __forceinline__ uint4 lds128(uint32_t a) {
    uint4 v; asm volatile("ld.shared.v4.u32 {%0,%1,%2,%3}, [%4];" : "=r"(v.x), "=r"(v.y), "=r"(v.z), "=r"(v.w) : "r"(a) : "memory"); return v;
}
__device__ __forceinline__ uint2 lds64(uint32_t a) {
    uint2 v; asm volatile("ld.shared.v2.u32 {%0,%1}, [%2];" : "=r"(v.x), "=r"(v.y) : "r"(a) : "memory"); return v;
}
__device__ __forceinline__ uint32_t lds32(uint32_t a) { uint32_t v; asm volatile("ld.shared.u32 %0, [%1];" : "=r"(v) : "r"(a) : "memory"); return v; }
__device__ __forceinline__ void sts128(uint32_t a, uint4 v) { asm volatile("st.shared.v4.u32 [%0], {%1,%2,%3,%4};" :: "r"(a), "r"(v.x), "r"(v.y), "r"(v.z), "r"(v.w) : "memory"); }
__device__ __forceinline__ void sts64(uint32_t a, uint32_t x, uint32_t y) { asm volatile("st.shared.v2.u32 [%0], {%1,%2};" :: "r"(a), "r"(x), "r"(y) : "memory"); }
__device__ __forceinline__ void sts32(uint32_t a, uint32_t x) { asm volatile("st.shared.u32 [%0], %1;" :: "r"(a), "r"(x) : "memory"); }
__device__ __forceinline__ float bf_lo(uint32_t x) { return __uint_as_float(x << 16); }
__device__ __forceinline__ float bf_hi(uint32_t x) { return __uint_as_float(x & 0xffff0000u); }
__device__ __forceinline__ uint32_t pack_bf16(float lo, float hi) { uint32_t d; asm("cvt.rn.bf16x2.f32 %0, %1, %2;" : "=r"(d) : "f"(hi), "f"(lo)); return d; }
__device__ __forceinline__ uint32_t pack_f16(float lo, float hi) { uint32_t d; asm("cvt.rn.f16x2.f32 %0, %1, %2;" : "=r"(d) : "f"(hi), "f"(lo)); return d; }
__device__ __forceinline__ uint32_t cvt_scaled(uint32_t x, uint32_t sc) { uint32_t y = bmul2(x, sc); return pack_f16(bf_lo(y), bf_hi(y)); }
__device__ __forceinline__ float pow2f(int e) { return __uint_as_float((uint32_t)(min(max(e, -126), 127) + 127) << 23); }
__device__ __forceinline__ uint32_t pow2bf2(int e) { return (uint32_t)(min(max(e, -126), 127) + 127) * 0x00800080u; }
__device__ __forceinline__ int bexp(uint32_t m) { return (int)(m >> 7) - 126; }

__device__ __forceinline__ void mbar_init(uint32_t a, int n) { asm volatile("mbarrier.init.shared::cta.b64 [%0], %1;" :: "r"(a), "r"(n) : "memory"); }
__device__ __forceinline__ void mbar_arrive(uint32_t a) { asm volatile("mbarrier.arrive.shared::cta.b64 _, [%0];" :: "r"(a) : "memory"); }
__device__ __forceinline__ void mbar_wait(uint32_t a) {
    uint32_t ok;
#pragma unroll 1
    for (int i = 0; i < SPIN_LIMIT; i++) {
        asm volatile("{.reg .pred p; mbarrier.try_wait.parity.shared::cta.b64 p, [%1], 0; selp.u32 %0, 1, 0, p;}" : "=r"(ok) : "r"(a) : "memory");
        if (ok) break;
    }
}
__device__ __forceinline__ void expect_tx(uint32_t bar, int n) { asm volatile("mbarrier.arrive.expect_tx.shared::cta.b64 _, [%0], %1;" :: "r"(bar), "r"(n) : "memory"); }
__device__ __forceinline__ void bulk(uint32_t dst, const void* src, int n, uint32_t bar) {
    asm volatile("cp.async.bulk.shared::cluster.global.mbarrier::complete_tx::bytes [%0], [%1], %2, [%3];" :: "r"(dst), "l"(src), "r"(n), "r"(bar) : "memory");
}
__device__ __forceinline__ void bar_sync(int id, int n) { asm volatile("bar.sync %0, %1;" :: "r"(id), "r"(n) : "memory"); }

#define WG_FENCE()  asm volatile("wgmma.fence.sync.aligned;" ::: "memory")
#define WG_COMMIT() asm volatile("wgmma.commit_group.sync.aligned;" ::: "memory")
#define WG_WAIT0()  asm volatile("wgmma.wait_group.sync.aligned 0;" ::: "memory")

template <int N>
__device__ __forceinline__ void wg_wait(uint32_t (&d)[34]) {
    asm volatile("wgmma.wait_group.sync.aligned %34;" : "+r"(d[0]), "+r"(d[1]), "+r"(d[2]), "+r"(d[3]), "+r"(d[4]), "+r"(d[5]), "+r"(d[6]), "+r"(d[7]), "+r"(d[8]), "+r"(d[9]), "+r"(d[10]), "+r"(d[11]), "+r"(d[12]), "+r"(d[13]), "+r"(d[14]), "+r"(d[15]), "+r"(d[16]), "+r"(d[17]), "+r"(d[18]), "+r"(d[19]), "+r"(d[20]), "+r"(d[21]), "+r"(d[22]), "+r"(d[23]), "+r"(d[24]), "+r"(d[25]), "+r"(d[26]), "+r"(d[27]), "+r"(d[28]), "+r"(d[29]), "+r"(d[30]), "+r"(d[31]), "+r"(d[32]), "+r"(d[33]) : "n"(N) : "memory");
}
template <int SCALE_D>
__device__ __forceinline__ void wgmma_rs(uint32_t (&d)[34], uint32_t a0, uint32_t a1, uint32_t a2, uint32_t a3, uint64_t desc) {
    asm volatile(
        "{\n.reg .pred p;\nsetp.ne.b32 p, %39, 0;\n"
        "wgmma.mma_async.sync.aligned.m64n136k16.f16.f16.f16 "
        "{%0,%1,%2,%3,%4,%5,%6,%7,%8,%9,%10,%11,%12,%13,%14,%15,%16,%17,%18,%19,%20,%21,%22,%23,%24,%25,%26,%27,%28,%29,%30,%31,%32,%33},"
        "{%34,%35,%36,%37}, %38, p, 1, 1, 1;\n}\n"
        : "+r"(d[0]), "+r"(d[1]), "+r"(d[2]), "+r"(d[3]), "+r"(d[4]), "+r"(d[5]), "+r"(d[6]), "+r"(d[7]), "+r"(d[8]), "+r"(d[9]), "+r"(d[10]), "+r"(d[11]), "+r"(d[12]), "+r"(d[13]), "+r"(d[14]), "+r"(d[15]), "+r"(d[16]), "+r"(d[17]), "+r"(d[18]), "+r"(d[19]), "+r"(d[20]), "+r"(d[21]), "+r"(d[22]), "+r"(d[23]), "+r"(d[24]), "+r"(d[25]), "+r"(d[26]), "+r"(d[27]), "+r"(d[28]), "+r"(d[29]), "+r"(d[30]), "+r"(d[31]), "+r"(d[32]), "+r"(d[33])
        : "r"(a0), "r"(a1), "r"(a2), "r"(a3), "l"(desc), "n"(SCALE_D));
}

__device__ __forceinline__ void wgmma_rs0(uint32_t (&d)[34], uint32_t a0, uint32_t a1, uint32_t a2, uint32_t a3, uint64_t desc) {
    asm volatile(
        "{\n.reg .pred p;\nsetp.ne.b32 p, %39, 0;\n"
        "wgmma.mma_async.sync.aligned.m64n136k16.f16.f16.f16 "
        "{%0,%1,%2,%3,%4,%5,%6,%7,%8,%9,%10,%11,%12,%13,%14,%15,%16,%17,%18,%19,%20,%21,%22,%23,%24,%25,%26,%27,%28,%29,%30,%31,%32,%33},"
        "{%34,%35,%36,%37}, %38, p, 1, 1, 1;\n}\n"
        : "=r"(d[0]), "=r"(d[1]), "=r"(d[2]), "=r"(d[3]), "=r"(d[4]), "=r"(d[5]), "=r"(d[6]), "=r"(d[7]), "=r"(d[8]), "=r"(d[9]), "=r"(d[10]), "=r"(d[11]), "=r"(d[12]), "=r"(d[13]), "=r"(d[14]), "=r"(d[15]), "=r"(d[16]), "=r"(d[17]), "=r"(d[18]), "=r"(d[19]), "=r"(d[20]), "=r"(d[21]), "=r"(d[22]), "=r"(d[23]), "=r"(d[24]), "=r"(d[25]), "=r"(d[26]), "=r"(d[27]), "=r"(d[28]), "=r"(d[29]), "=r"(d[30]), "=r"(d[31]), "=r"(d[32]), "=r"(d[33])
        : "r"(a0), "r"(a1), "r"(a2), "r"(a3), "l"(desc), "n"(0));
}

__device__ __forceinline__ int kappa_inv(int k) { return (k & 0x61) | ((k >> 2) & 6) | ((k & 6) << 2); }

__device__ __forceinline__ void st_rec(uint4* p, float m, float l, float a, uint32_t tag) {
    asm volatile("{.reg .b128 t; .reg .b64 x, y; mov.b64 x, {%1, %2}; mov.b64 y, {%3, %4}; mov.b128 t, {x, y}; st.relaxed.gpu.global.b128 [%0], t;}"
                 :: "l"(p), "r"(__float_as_uint(m)), "r"(__float_as_uint(l)), "r"(__float_as_uint(a)), "r"(tag) : "memory");
}
__device__ __forceinline__ uint4 ld_rec(const uint4* p) {
    uint4 v;
    asm volatile("{.reg .b128 t; .reg .b64 x, y; ld.relaxed.gpu.global.b128 t, [%4]; mov.b128 {x, y}, t; mov.b64 {%0, %1}, x; mov.b64 {%2, %3}, y;}"
                 : "=r"(v.x), "=r"(v.y), "=r"(v.z), "=r"(v.w) : "l"(p) : "memory");
    return v;
}
__device__ __forceinline__ uint32_t dp2a_lo8(uint32_t o, uint32_t c) { uint32_t d; asm("dp2a.lo.u32.u32 %0, %1, %2, %3;" : "=r"(d) : "r"(o), "r"(0x0008u), "r"(c)); return d; }
__device__ __forceinline__ uint32_t dp2a_hi8(uint32_t o, uint32_t c) { uint32_t d; asm("dp2a.lo.u32.u32 %0, %1, %2, %3;" : "=r"(d) : "r"(o), "r"(0x0800u), "r"(c)); return d; }

#define TS(k)
__device__ __forceinline__ float ex2(float x) { float y; asm("ex2.approx.ftz.f32 %0, %1;" : "=f"(y) : "f"(x)); return y; }
__device__ __forceinline__ uint32_t ldcg32(const void* p) { uint32_t v; asm volatile("ld.global.cg.u32 %0, [%1];" : "=r"(v) : "l"(p) : "memory"); return v; }
__device__ __forceinline__ uint32_t ld_relaxed32(const void* p) { uint32_t v; asm volatile("ld.relaxed.gpu.global.u32 %0, [%1];" : "=r"(v) : "l"(p) : "memory"); return v; }
__device__ __forceinline__ void warp_arrive(uint32_t bar) { __syncwarp(); if ((threadIdx.x & 31) == 0) mbar_arrive(bar); }

struct Row { uint4 z0, z1, z2; uint32_t z3; };
__device__ __forceinline__ void load_row(Row& w, uint32_t ent) {
    const uint4* row = g_idx9 + (ent >> 8) * 4;
    w.z0 = ldcg128(row); w.z1 = ldcg128(row + 1); w.z2 = ldcg128(row + 2); w.z3 = ldcg32(row + 3);
}
__device__ __forceinline__ void row_slots(const Row& w, int v0, uint32_t ent, bool plain, uint32_t (&o)[13]) {
    const int vl = ent & 7;
    const uint32_t k1 = ((uint32_t)(vl - 9 * v0) & 0xffffu) * 0x10001u;
    const uint32_t k2 = ((uint32_t)(vl - 9 * v0 + 9 * V_) & 0xffffu) * 0x10001u;
    const uint32_t sent = (uint32_t)(511 * 9 + vl) * 0x10001u;
    const uint32_t z[13] = {w.z0.x, w.z0.y, w.z0.z, w.z0.w, w.z1.x, w.z1.y, w.z1.z, w.z1.w, w.z2.x, w.z2.y, w.z2.z, w.z2.w, w.z3};
#pragma unroll
    for (int k = 0; k < 13; k++) o[k] = __viaddmin_u16x2(z[k], k2, __viaddmin_u16x2(z[k], k1, sent));
    const int self = plain ? (int)(ent >> 4) & 15 : -1;
    const uint32_t keep = (ent & 8) ? 0x0000ffffu : 0xffff0000u;
#pragma unroll
    for (int k = 0; k < 13; k++) if (k == self) o[k] = (o[k] & keep) | (sent & ~keep);
}
template <int K0, int N>
__device__ __forceinline__ void lookup_part(const uint32_t (&o)[13], uint32_t sES, uint32_t ml, float& m, float& l, float& a) {
    float e[2 * N], s[2 * N];
#pragma unroll
    for (int k = 0; k < N; k++) {
        const uint2 x = lds64(dp2a_lo8(o[K0 + k], sES)), y = lds64(dp2a_hi8(o[K0 + k], sES));
        e[2 * k] = __uint_as_float(x.x); s[2 * k] = __uint_as_float(x.y);
        e[2 * k + 1] = __uint_as_float(y.x); s[2 * k + 1] = __uint_as_float(y.y);
    }
    if (ml) {
#pragma unroll
        for (int k = 0; k < (N + 1) / 2; k++) {
            uint4 v = lds128(ml + K0 * 8 + 16 * k);
            e[4 * k] += __uint_as_float(v.x); e[4 * k + 1] += __uint_as_float(v.y);
            if (4 * k + 2 < 2 * N) { e[4 * k + 2] += __uint_as_float(v.z); e[4 * k + 3] += __uint_as_float(v.w); }
        }
    }
    float m0 = m, m1 = -INFINITY;
#pragma unroll
    for (int k = 0; k < N; k++) { m0 = fmaxf(m0, e[2 * k]); m1 = fmaxf(m1, e[2 * k + 1]); }
    const float mn = fmaxf(m0, m1);
    const float ms = (mn == -INFINITY) ? 0.f : mn;
    float l0 = 0.f, l1 = 0.f, a0 = 0.f, a1 = 0.f;
    if (K0 > 0) { const float c = ex2(m - ms); l0 = l * c; a0 = a * c; }
#pragma unroll
    for (int k = 0; k < N; k++) {
        const float w0 = ex2(e[2 * k] - ms), w1 = ex2(e[2 * k + 1] - ms);
        l0 += w0; a0 = fmaf(w0, s[2 * k], a0);
        l1 += w1; a1 = fmaf(w1, s[2 * k + 1], a1);
    }
    m = mn; l = l0 + l1; a = a0 + a1;
}
__device__ __noinline__ void lookup_fn(uint32_t o0, uint32_t o1, uint32_t o2, uint32_t o3, uint32_t o4, uint32_t o5, uint32_t o6, uint32_t o7, uint32_t o8,
                                       uint32_t o9, uint32_t o10, uint32_t o11, uint32_t o12, uint32_t sb, uint32_t ent, uint32_t tag, bool plain) {
    const uint32_t o[13] = {o0, o1, o2, o3, o4, o5, o6, o7, o8, o9, o10, o11, o12};
    const uint32_t i = (ent >> 3) & 31, ml = plain ? 0u : sb + OFF_ML + i * 112;
    float m = -INFINITY, l = 0.f, a = 0.f;
    lookup_part<0, 6>(o, sb + OFF_ES, ml, m, l, a);
    lookup_part<6, 7>(o, sb + OFF_ES, ml, m, l, a);
    st_rec(g_part + (ent >> 8) * 32 + i, m, l, a, tag);
}
__device__ __forceinline__ void lookup(const uint32_t (&o)[13], uint32_t sb, uint32_t ent, uint32_t tag, bool plain) {
    lookup_fn(o[0], o[1], o[2], o[3], o[4], o[5], o[6], o[7], o[8], o[9], o[10], o[11], o[12], sb, ent, tag, plain);
}
__device__ __forceinline__ void staged_lookup(uint32_t sb, int x, uint32_t tag, bool plain) {
    uint32_t o[13], ent;
#pragma unroll
    for (int k = 0; k < 7; k++) {
        uint2 v = lds64(sb + OFF_X + (k * XCAP + x) * 8);
        o[2 * k] = v.x; if (k < 6) o[2 * k + 1] = v.y; else ent = v.y;
    }
    lookup(o, sb, ent, tag, plain);
}
__device__ __forceinline__ void combine(__nv_bfloat16* out, uint32_t tag) {
    const int warp = threadIdx.x >> 5, lane = threadIdx.x & 31;
    const int r0 = 3 * warp, b0 = blockIdx.x * 32 + r0;
    bar_sync(3, NTHR);
    if (threadIdx.x == 0) {
        const bool last = blockIdx.x < NOWN && atomicAdd(&g_done, 1u) + 1 == tag * NOWN;
        if (last) atomicAdd(&g_epoch, 1u);
#pragma unroll 1
        for (int it = last ? SPIN_LIMIT : 0; it < SPIN_LIMIT; it++) {
            if ((int)(ld_relaxed32(&g_done) - tag * NOWN) >= 0) break;
            __nanosleep(40);
        }
    }
    bar_sync(3, NTHR);
    if (r0 >= 32) return;
    const bool on = lane < F_, third = r0 + 2 < 32;
    const uint4* p = g_part + b0 * 32 + lane;
    uint4 rec[3];
#pragma unroll
    for (int r = 0; r < 3; r++) rec[r] = make_uint4(0, 0, 0, (on && (r < 2 || third)) ? ~tag : tag);
#pragma unroll 1
    for (int it = 0; it < SPIN_LIMIT; it++) {
#pragma unroll
        for (int r = 0; r < 3; r++) if (rec[r].w != tag) rec[r] = ld_rec(p + 32 * r);
        if (it == 0) TS(28);
        if (__all_sync(0xffffffffu, rec[0].w == tag && rec[1].w == tag && rec[2].w == tag)) break;
        __nanosleep(100);
    }
    TS(29 + (threadIdx.x >> 7));
    float l[3], a[3];
#pragma unroll
    for (int r = 0; r < 3; r++) {
        const float m = on ? __uint_as_float(rec[r].x) : -INFINITY;
        int key = __float_as_int(m); key ^= (key >> 31) & 0x7fffffff;
        key = __reduce_max_sync(0xffffffffu, key); key ^= (key >> 31) & 0x7fffffff;
        const float c = ex2(m - __int_as_float(key));
        l[r] = __uint_as_float(rec[r].y) * c; a[r] = __uint_as_float(rec[r].z) * c;
    }
#pragma unroll
    for (int o = 16; o; o >>= 1)
#pragma unroll
        for (int r = 0; r < 3; r++) { l[r] += __shfl_xor_sync(0xffffffffu, l[r], o); a[r] += __shfl_xor_sync(0xffffffffu, a[r], o); }
    if (lane < 2 || (lane == 2 && third)) {
        const float ll = lane == 0 ? l[0] : lane == 1 ? l[1] : l[2], aa = lane == 0 ? a[0] : lane == 1 ? a[1] : a[2];
        out[b0 + lane] = __float2bfloat16(__fdividef(aa, ll));
    }
}

struct Tile { uint32_t rr0, rr1; float mul; int pos; };

struct Mma {
    uint32_t bb[16], hh[16], f0[16], f1[16], cu[16], a[32];
    uint32_t rv0, rv1, sb, pu, sx, sy;
    uint4 px; uint32_t ps; float pm; int pp;
    float cv, ce, cs;
    int pos, vp, tsw;
    uint64_t desc;

    __device__ __forceinline__ void set_v(int slab) {
        const int q = threadIdx.x & 3, g = (threadIdx.x >> 2) & 7;
        const uint32_t p = sb + OFF_T + vp * 512 + q * 16;
#pragma unroll
        for (int m = 0; m < 4; m++) {
            uint4 x = lds128(p + m * 64), y = lds128(p + 256 + (m ^ 1) * 64);
            f0[4 * m] = x.x; f0[4 * m + 1] = x.y; f0[4 * m + 2] = x.z; f0[4 * m + 3] = x.w;
            f1[4 * m] = y.x; f1[4 * m + 1] = y.y; f1[4 * m + 2] = y.z; f1[4 * m + 3] = y.w;
        }
        const uint4 s = lds128(sb + OFF_SC + vp * 16);
        rv0 = s.x; rv1 = s.z; cv = __uint_as_float((q & 1) ? s.w : s.y);
        const int r = 8 * slab + 2 * vp + g;
        pu = sb + OFF_T + r * 256 + q * 16 + (g & 1) * 64;
        pos = (8 * slab + g - (q & 1)) * 65536 + r * 72 + (2 * vp + (q & 1)) * 8;
    }
    __device__ __forceinline__ void load_u() {
        const uint32_t p1 = pu ^ 64;
        uint4 x = lds128(pu), y = lds128(p1), z = lds128(pu + 128), v = lds128(p1 + 128);
        cu[0] = x.x; cu[1] = x.y; cu[2] = x.z; cu[3] = x.w; cu[4] = y.x; cu[5] = y.y; cu[6] = y.z; cu[7] = y.w;
        cu[8] = z.x; cu[9] = z.y; cu[10] = z.z; cu[11] = z.w; cu[12] = v.x; cu[13] = v.y; cu[14] = v.z; cu[15] = v.w;
        const uint2 s = lds64((((pu - sb - OFF_T) >> 8) << 3) + sb + OFF_SC);
        sx = s.x; sy = s.y;
    }
    __device__ __forceinline__ void issue(uint32_t (&acc)[34], uint32_t (&old)[34], Tile& n, int tn) {
#pragma unroll
        for (int k = 0; k < 16; k++) { a[2 * k] = hmul2(cu[k], f0[k]); a[2 * k + 1] = hmul2(cu[k], f1[k]); }
        WG_FENCE();
        wgmma_rs0(acc, a[0], a[1], a[2], a[3], desc);
#pragma unroll
        for (int s = 1; s < 8; s++) wgmma_rs<1>(acc, a[4 * s], a[4 * s + 1], a[4 * s + 2], a[4 * s + 3], desc + (uint64_t)(s * (2 * WLBO >> 4)));
        WG_COMMIT();
        wg_wait<1>(old);
        n.rr0 = hmul2(sx, rv0); n.rr1 = hmul2(sx, rv1); n.mul = __uint_as_float(sy) * cv; n.pos = pos;
        pu += 32 * 256; pos += 32 * 65536 + 32 * 72;
        if (tn == tsw) {
            const int wg = threadIdx.x >> 7, w = (threadIdx.x >> 5) & 3, k = 4 * tn + w, first = vp < 2;
            vp = first ? 2 : 3; tsw = (wg && w) ? 23 : 24; if (!first) tsw = -1;
            set_v(k - (first ? (wg ? 30 : 63) : (wg ? 61 : 96))); TS(wg * 8 + (first ? 3 : 4));
        }
        if (tn < 15) mbar_wait(sb + OFF_BAR + (BAR_CONV + tn + 1) * 8);
    }
    __device__ __forceinline__ void flush(int t) {
        const uint32_t x = hadd2(hadd2(px.x, px.y), hadd2(px.z, px.w));
        const uint32_t y = __byte_perm(x, ps, (threadIdx.x & 1) ? 0x7632 : 0x5410);
        const __half2 h2 = *reinterpret_cast<const __half2*>(&y);
        float e = __low2float(h2) * ce * pm;
        const float s = __high2float(h2) * cs * pm;
        const uint32_t d = (uint32_t)pp >> 16;
        e -= (d == 0 || d == 500) ? 1.f : 0.f;
        e = d > 500u ? -INFINITY : e;
        sts64(sb + OFF_ES + (pp & 0xffff), __float_as_uint(e), __float_as_uint(s));
        asm volatile("{.reg .pred p; setp.eq.s32 p, %1, 15; setp.eq.or.s32 p, %1, 23, p; @p mbarrier.arrive.shared::cta.b64 _, [%0];}"
                     :: "r"(sb + OFF_BAR + BAR_GRP * 8 + (t & 16) / 2), "r"(t) : "memory");
    }
    template <bool NEXT>
    __device__ __forceinline__ void epilogue(const uint32_t (&acc)[34], const Tile& c, int t) {
        flush(t - 1);
        uint32_t e0 = 0, e1 = 0, e2 = 0, e3 = 0;
#pragma unroll
        for (int j = 0; j < 16; j += 2) {
            e0 = hfma2(hfma2_relu(bb[j], c.rr0, acc[2 * j]), hh[j], e0);
            e1 = hfma2(hfma2_relu(bb[j], c.rr1, acc[2 * j + 1]), hh[j], e1);
            e2 = hfma2(hfma2_relu(bb[j + 1], c.rr0, acc[2 * j + 2]), hh[j + 1], e2);
            e3 = hfma2(hfma2_relu(bb[j + 1], c.rr1, acc[2 * j + 3]), hh[j + 1], e3);
            if (j == 4 && NEXT) load_u();
        }
        e0 = hadd2(e0, e2); e1 = hadd2(e1, e3);
        sts32(sb + OFF_Q + threadIdx.x * 4, hadd2(__byte_perm(e0, e1, 0x5410), __byte_perm(e0, e1, 0x7632)));
        __syncwarp();
        px = lds128(sb + OFF_Q + (threadIdx.x & ~3) * 4);
        ps = __byte_perm(acc[32], acc[33], 0x5410);
        pm = c.mul; pp = c.pos;
    }
};

__device__ __forceinline__ void fetch_raw(uint32_t sb, const uint8_t* table, int v0, int r0) {
    const int lane = threadIdx.x & 31;
    if (r0 < 512) {
#pragma unroll 1
        for (int k = 0; k < 4; k++) {
            const int r = r0 + 8 * k, u = v0 + r - (v0 + r >= V_ ? V_ : 0);
#pragma unroll
            for (int z = 0; z < 4; z++)
                asm volatile("cp.async.cg.shared.global [%0], [%1], 16;" :: "r"(sb + OFF_T + r * 256 + lane * 16 + z * 512), "l"(table + u * 256 + lane * 16 + z * 512) : "memory");
        }
    }
    asm volatile("cp.async.commit_group;" ::: "memory");
}
__device__ __forceinline__ uint32_t row_max(uint32_t sb, int r) {
    const uint32_t p = sb + OFF_T + r * 256;
    uint32_t m0 = 0, m1 = 0;
#pragma unroll 8
    for (int k = 0; k < 16; k++) {
        const uint4 x = lds128(p + (((k + r) & 15) << 4));
        m0 = babsmax2(m0, babsmax2(x.x, x.y)); m1 = babsmax2(m1, babsmax2(x.z, x.w));
    }
    return babsmax2(m0, m1);
}
__device__ __forceinline__ void convert_row(uint32_t sb, int r, uint32_t mx, int amin) {
    const uint32_t p = sb + OFF_T + r * 256;
    const int a = min(max(bexp(bmag(mx)), amin), 126);
    const uint32_t sc = pow2bf2(-a), sw = (r & 1) << 6;
    const float rho = pow2f(amin - a);
    sts64(sb + OFF_SC + r * 8, pack_f16(rho, rho), __float_as_uint(pow2f(a)));
#pragma unroll 1
    for (int hf = 0; hf < 2; hf++) {
        uint4 x[8];
#pragma unroll
        for (int k = 0; k < 8; k++) x[k] = lds128(p + hf * 128 + (((k + r) & 7) << 4));
#pragma unroll
        for (int k = 0; k < 8; k++)
            sts128(p + hf * 128 + ((((k + r) & 7) << 4) ^ sw), make_uint4(cvt_scaled(x[k].x, sc), cvt_scaled(x[k].y, sc), cvt_scaled(x[k].z, sc), cvt_scaled(x[k].w, sc)));
    }
}
__device__ __forceinline__ uint32_t fetch_entry(int n, int limit, int pre, int base) {
    int lo = 0;
#pragma unroll
    for (int s = 16; s; s >>= 1) { const int pc = __shfl_sync(0xffffffffu, pre, lo + s); if (pc <= n) lo += s; }
    const int bs = __shfl_sync(0xffffffffu, base, lo);
    return n < limit ? ldcg32((const uint32_t*)g_sorted + bs + n) : 0u;
}

__device__ __forceinline__ void router(const int* __restrict__ idx, uint8_t* smem, uint32_t tag) {
    const int tid = threadIdx.x, rt = blockIdx.x - NOWN;
    const int row0 = rt * RROWS, n4 = (min(B_, row0 + RROWS) - row0) * F_ / 4;
    uint32_t* hist = (uint32_t*)smem;
    uint32_t* wsum = hist + 384;
    uint32_t* sorted = (uint32_t*)(smem + 2048);
    uint32_t v[40], en[40];
#pragma unroll
    for (int k = 0; k < 10; k++) {
        uint4 x = make_uint4(0, 0, 0, 0);
        if (tid + k * NTHR < n4) x = ldg128(idx + row0 * F_ + (tid + k * NTHR) * 4);
        v[4 * k] = x.x; v[4 * k + 1] = x.y; v[4 * k + 2] = x.z; v[4 * k + 3] = x.w;
    }
    hist[tid] = 0;
    __syncthreads(); TS(2);
#pragma unroll
    for (int k = 0; k < 40; k += 2) {
        const int x = (tid + (k >> 2) * NTHR) * 2 + ((k >> 1) & 1);
        if (x < 2 * n4) {
            const uint32_t rw = row0 + x / 13, i2 = x % 13;
            const uint32_t u0 = min(v[k], (uint32_t)(V_ - 1)), u1 = min(v[k + 1], (uint32_t)(V_ - 1));
            ((uint32_t*)g_idx9)[rw * 16 + i2] = (u0 | u1 << 16) * 9;
            const uint32_t k0 = (u0 >> 3) * 3 + max(((int)(u0 >> 1) & 3) - 1, 0), k1 = (u1 >> 3) * 3 + max(((int)(u1 >> 1) & 3) - 1, 0);
            en[k] = rw << 8 | i2 << 4 | (u0 & 7); en[k + 1] = rw << 8 | i2 << 4 | 8 | (u1 & 7);
            v[k] = k0 << 16 | atomicAdd(&hist[k0], 1u); v[k + 1] = k1 << 16 | atomicAdd(&hist[k1], 1u);
        }
    }
    __syncthreads();
    const uint32_t cnt = hist[tid]; TS(3);
    uint32_t inc = cnt;
#pragma unroll
    for (int o = 1; o < 32; o <<= 1) { const uint32_t y = __shfl_up_sync(0xffffffffu, inc, o); if ((tid & 31) >= o) inc += y; }
    if ((tid & 31) == 31) wsum[tid >> 5] = inc;
    __syncthreads();
    uint32_t start = inc - cnt;
    for (int k = 0; k < (tid >> 5); k++) start += wsum[k];
    hist[tid] = start;
    __syncthreads();
#pragma unroll
    for (int k = 0; k < 40; k++)
        if (tid + (k >> 2) * NTHR < n4) sorted[hist[v[k] >> 16] + (v[k] & 0xffffu)] = en[k];
    __syncthreads();
    for (int c = tid; c < n4; c += NTHR) g_sorted[rt * (SEG / 4) + c] = ((const uint4*)sorted)[c];
    __syncthreads();
    if (tid < NOWN * 3) {
        __threadfence();
        asm volatile("st.relaxed.gpu.global.u64 [%0], %1;" :: "l"(g_desc + (tid / 3) * 32 + (tid % 3) * NROUTE + rt),
                     "l"((unsigned long long)tag << 32 | cnt << 16 | start) : "memory");
    }
}

__global__ void __launch_bounds__(NTHR, 1)
afm_kernel(const int* __restrict__ idx, const uint8_t* __restrict__ table, const int* __restrict__ ii, const int* __restrict__ jj,
           const uint8_t* __restrict__ W, const uint8_t* __restrict__ bias, const uint8_t* __restrict__ hvec,
           const uint8_t* __restrict__ pvec, __nv_bfloat16* __restrict__ out) {
    extern __shared__ __align__(1024) uint8_t smem[];
    const uint32_t sb = smem_u32(smem);
    const int tid = threadIdx.x, lane = tid & 31, g = lane >> 2, q = lane & 3;
    if (blockIdx.x >= NOWN) {
        TS(0); const uint32_t tag = ld_relaxed32(&g_epoch) + 1;
        router(idx, smem, tag); TS(1);
        if (blockIdx.x < B_ / 32) combine(out, tag); TS(4);
        return;
    }
    const int v0 = blockIdx.x * 8;
    if (tid < 256) {
#pragma unroll
        for (int k = 0; k < 8; k++) asm volatile("cp.async.cg.shared.global [%0], [%1], 16;" :: "r"(sb + OFF_ES + tid * 16 + k * 4096), "l"(W + tid * 16 + k * 4096) : "memory");
        const uint8_t* src = tid < 16 ? bias : tid < 32 ? hvec : pvec;
        if (tid < 48) asm volatile("cp.async.cg.shared.global [%0], [%1], 16;" :: "r"(sb + OFF_ES + 32768 + tid * 16), "l"(src + (tid & 15) * 16) : "memory");
    }
    if (tid < 256) {
        asm volatile("setmaxnreg.inc.sync.aligned.u32 208;");
        Mma c;
        const int wg = tid >> 7, w = (tid >> 5) & 3;
        c.sb = sb;
        asm volatile("cp.async.wait_all;" ::: "memory");
        bar_sync(0, 384);
        TS(wg * 8 + 2);
        const uint32_t ch = ((tid >> 3) + tid) & 15, pw = sb + OFF_ES + kappa_inv((tid & 7) | wg << 3) * 256 + ch * 16;
        const uint2 b4 = lds64(sb + OFF_ES + 32768 + lane * 8), h4 = lds64(sb + OFF_ES + 33024 + lane * 8), p4 = lds64(sb + OFF_ES + 33280 + lane * 8);
        const uint32_t pv = lds32(sb + OFF_ES + 33280 + (kappa_inv(tid & 127) >> 1) * 4);
        uint32_t mw = 0;
#pragma unroll 1
        for (int k = 0; k < 2; k++) {
#pragma unroll
            for (int z = 0; z < 4; z++) { const uint4 x = lds128(sb + OFF_ES + tid * 16 + (4 * k + z) * 4096); mw = babsmax2(mw, babsmax2(babsmax2(x.x, x.y), babsmax2(x.z, x.w))); }
        }
        mw = __reduce_max_sync(0xffffffffu, bmag(mw));
        if (lane == 0) sts32(sb + OFF_MISC + (tid >> 5) * 4, mw);
        const uint32_t mb = __reduce_max_sync(0xffffffffu, bmag(babsmax2(b4.x, b4.y)));
        const uint32_t mh = __reduce_max_sync(0xffffffffu, bmag(babsmax2(h4.x, h4.y)));
        const uint32_t mp = __reduce_max_sync(0xffffffffu, bmag(babsmax2(p4.x, p4.y)));
        bar_sync(1, 256);
        mw = __reduce_max_sync(0xffffffffu, lds32(sb + OFF_MISC + (lane & 7) * 4));
        const int ew = max(bexp(mw) - 7, -100), ed = max(bexp(mh) + 7, -100), ep = max(bexp(mp) - 8, -100);
        const int amin = min(max((bexp(mb) - 13 - ew) >> 1, -60), 126);
        if (tid == 0) { sts32(sb + OFF_MISC + 32, (uint32_t)amin); mbar_arrive(sb + OFF_BAR + BAR_SCALE * 8); }
        const uint32_t sw = pow2bf2(-ew);
#pragma unroll 1
        for (int k = 0; k < 4; k++) {
#pragma unroll
            for (int z = 0; z < 2; z++) {
                const uint4 x = lds128(pw + k * 8192 + z * 1024);
                sts128(sb + OFF_W + (4 * k + 2 * z + wg) * WLBO + ch * 128 + (tid & 7) * 16,
                       make_uint4(cvt_scaled(x.x, sw), cvt_scaled(x.y, sw), cvt_scaled(x.z, sw), cvt_scaled(x.w, sw)));
            }
        }
        if (tid < 128) {
            const uint32_t y = __byte_perm(cvt_scaled(pv, pow2bf2(-ep)), 0, (tid & 1) ? 0x3232 : 0x1010);
            sts128(sb + OFF_W + (tid >> 3) * WLBO + 2048 + (tid & 7) * 16, make_uint4(y, y, y, y));
        } else if (tid < 160) {
            const int eb = -2 * amin - ew;
            const float s1 = pow2f(eb >> 1), s2 = pow2f(eb - (eb >> 1));
            const uint32_t sh = pow2bf2(-ed), dst = sb + OFF_L + (lane & 1) * 128 + (lane >> 1) * 4;
            sts32(dst, pack_f16(bf_lo(b4.x) * s1 * s2, bf_hi(b4.x) * s1 * s2)); sts32(dst + 64, pack_f16(bf_lo(b4.y) * s1 * s2, bf_hi(b4.y) * s1 * s2));
            sts32(dst + 256, cvt_scaled(h4.x, sh)); sts32(dst + 320, cvt_scaled(h4.y, sh));
        }
        asm volatile("fence.proxy.async.shared::cta;" ::: "memory");
        c.ce = pow2f(ew + ed) * LOG2E; c.cs = pow2f(ep);
        c.desc = (uint64_t)(((sb + OFF_W) & 0x3FFFF) >> 4) | ((uint64_t)(WLBO >> 4) << 16) | ((uint64_t)(128 >> 4) << 32);
        c.vp = wg; c.tsw = w == 3 ? 15 : 16;
        c.px = make_uint4(0, 0, 0, 0); c.ps = 0; c.pm = 0.f; c.pp = 64;
        bar_sync(1, 256);
#pragma unroll
        for (int m = 0; m < 4; m++) {
            const uint4 x = lds128(sb + OFF_L + q * 64 + m * 16), y = lds128(sb + OFF_L + 256 + q * 64 + m * 16);
            c.bb[4 * m] = x.x; c.bb[4 * m + 1] = x.y; c.bb[4 * m + 2] = x.z; c.bb[4 * m + 3] = x.w;
            c.hh[4 * m] = y.x; c.hh[4 * m + 1] = y.y; c.hh[4 * m + 2] = y.z; c.hh[4 * m + 3] = y.w;
        }
        warp_arrive(sb + OFF_BAR + BAR_WDONE * 8);
        TS(wg * 8 + 1);
#pragma unroll 1
        for (int k = 0; k < 2; k++) mbar_wait(sb + OFF_BAR + (BAR_CONV + k) * 8);
        c.set_v(w); c.load_u(); TS(wg * 8);
        uint32_t acc0[34], acc1[34];
        Tile t0, t1;
        c.issue(acc0, acc0, t0, 1); c.load_u();
#pragma unroll 1
        for (int t = 0; t < 30; t += 2) {
            WG_WAIT0(); c.issue(acc1, acc0, t1, t + 2); c.epilogue<true>(acc0, t0, t);
            WG_WAIT0(); c.issue(acc0, acc1, t0, t + 3); c.epilogue<true>(acc1, t1, t + 1);
        }
        WG_WAIT0();
        if (wg == 0) {
            c.issue(acc1, acc0, t1, 32); c.epilogue<false>(acc0, t0, 30);
            wg_wait<0>(acc1); c.epilogue<false>(acc1, t1, 31); c.flush(0);
        } else {
            wg_wait<0>(acc0); c.epilogue<false>(acc0, t0, 30); c.flush(0);
        }
        warp_arrive(sb + OFF_BAR + (BAR_GRP + 2) * 8); TS(wg * 8 + 5);
        asm volatile("setmaxnreg.dec.sync.aligned.u32 88;");
    } else {
        asm volatile("setmaxnreg.dec.sync.aligned.u32 88;");
        const int ht = tid - 256, hw = ht >> 5;
        fetch_raw(sb, table, v0, 32 * hw);
        if (ht < 31) mbar_init(sb + OFF_BAR + ht * 8, (ht == BAR_GRP + 2 || ht == BAR_WDONE) ? 8 : (ht == BAR_GRP || ht == BAR_GRP + 1) ? 256 : ht == BAR_STAGE ? 4 : 1);
        asm volatile("bar.arrive 0, 384;" ::: "memory");
        bar_sync(2, 128); TS(24);
        int amin = 0;
#pragma unroll 1
        for (int j = 0; j < 4; j++) {
            fetch_raw(sb, table, v0, 128 * j + 128 + 32 * hw);
            asm volatile("cp.async.wait_group 1;" ::: "memory");
            __syncwarp();
            const uint32_t mx = row_max(sb, 128 * j + ht);
            if (j == 0) { mbar_wait(sb + OFF_BAR + BAR_SCALE * 8); amin = (int)lds32(sb + OFF_MISC + 32); TS(16); }
            convert_row(sb, 128 * j + ht, mx, amin);
            warp_arrive(sb + OFF_BAR + (BAR_CONV + 4 * j + hw) * 8);
        }
        uint32_t* ml = (uint32_t*)(smem + OFF_ML); TS(17);
        const uint32_t tag = ld_relaxed32(&g_epoch) + 1;
        int pi[3], pj[3];
#pragma unroll
        for (int k = 0; k < 3; k++) { pi[k] = __ldg(ii + min(ht + 128 * k, P_ - 1)); pj[k] = __ldg(jj + min(ht + 128 * k, P_ - 1)); }
        mbar_wait(sb + OFF_BAR + BAR_WDONE * 8);
#pragma unroll 1
        for (int k = ht; k < F_ * 28; k += 128) ml[k] = 0;
        if (ht < 64) {
            const int vl = ht & 7, x = ht >> 3, r = x < (vl & 6) ? x : x + 504;
            sts64(sb + OFF_ES + r * 72 + vl * 8, 0xff800000u, 0u);
        }
        bar_sync(2, 128);
#pragma unroll
        for (int k = 0; k < 3; k++)
            if (ht + 128 * k < P_) { atomicAdd(&ml[pi[k] * 28 + pj[k]], 1u); atomicAdd(&ml[pj[k] * 28 + pi[k]], 1u); }
        bar_sync(2, 128);
        int odd = 0;
#pragma unroll 1
        for (int k = ht; k < F_ * 28; k += 128) {
            const uint32_t c = ml[k];
            odd |= (k % 28 < F_) && c != (k % 29 != 0);
            ml[k] = __float_as_uint(__log2f((float)c));
        }
        asm volatile("{.reg .pred p; setp.ne.s32 p, %0, 0; barrier.red.or.pred p, 2, 128, p; selp.s32 %0, 1, 0, p;}" : "+r"(odd) :: "memory");
        const bool plain = !odd;
        unsigned long long ds = 0;
#pragma unroll 1
        for (int it = 0; it < SPIN_LIMIT; it++) {
            if (lane < 21) asm volatile("ld.acquire.gpu.global.u64 %0, [%1];" : "=l"(ds) : "l"(g_desc + blockIdx.x * 32 + lane) : "memory");
            if (__all_sync(0xffffffffu, lane >= 21 || (uint32_t)(ds >> 32) == tag)) break;
            __nanosleep(100);
        }
        const int cnt = (uint32_t)(ds >> 32) == tag ? (int)((ds >> 16) & 0xffff) : 0; TS(18);
        int inc = cnt;
#pragma unroll
        for (int o = 1; o < 32; o <<= 1) { const int y = __shfl_up_sync(0xffffffffu, inc, o); if (lane >= o) inc += y; }
        const int nA = __shfl_sync(0xffffffffu, inc, 6), nAB = __shfl_sync(0xffffffffu, inc, 13), nT = __shfl_sync(0xffffffffu, inc, 20);
        const int base = (lane % NROUTE) * SEG + (int)(ds & 0xffff) - (inc - cnt);
        const int pre = lane < 21 ? inc - cnt : 0x3fffffff;
        const int nst = max(min(min(nT, LCAP) - nAB, XCAP), 0), nl = min(nAB, LCAP);
        {
            int sp[6], sn[6], sbs[6];
            uint32_t en[6][2];
#pragma unroll
            for (int k = 0; k < 6; k++) {
                const int sg = (20 - hw - 4 * k) & 31;
                sp[k] = __shfl_sync(0xffffffffu, pre, sg) + lane; sn[k] = min(__shfl_sync(0xffffffffu, inc, sg), LCAP);
                sbs[k] = __shfl_sync(0xffffffffu, base, sg);
            }
#pragma unroll
            for (int k = 0; k < 6; k++)
#pragma unroll
                for (int z = 0; z < 2; z++) if (sp[k] + 32 * z < sn[k]) en[k][z] = ldcg32((const uint32_t*)g_sorted + sbs[k] + sp[k] + 32 * z);
#pragma unroll
            for (int k = 0; k < 6; k++) {
#pragma unroll
                for (int z = 0; z < 2; z++) if (sp[k] + 32 * z < sn[k]) sts32(sb + OFF_L + (sp[k] + 32 * z) * 4, en[k][z]);
#pragma unroll 1
                for (int n = sp[k] + 64; n < sn[k]; n += 32) sts32(sb + OFF_L + n * 4, ldcg32((const uint32_t*)g_sorted + sbs[k] + n));
            }
        }
        bar_sync(2, 128);
        uint32_t o[13];
        Row w;
        {
            uint32_t en[3];
#pragma unroll
            for (int k = 0; k < 3; k++) en[k] = ht + 128 * k < nst ? lds32(sb + OFF_L + (nAB + ht + 128 * k) * 4) : 0u;
#pragma unroll
            for (int k = 0; k < 3; k++) {
                if (ht + 128 * k < nst) {
                    load_row(w, en[k]); row_slots(w, v0, en[k], plain, o);
#pragma unroll
                    for (int z = 0; z < 7; z++) sts64(sb + OFF_X + (z * XCAP + ht + 128 * k) * 8, o[2 * z], z < 6 ? o[2 * z + 1] : en[k]);
                }
            }
        }
        if (ht == 0) sts64(sb + OFF_MISC + 40, tag, (uint32_t)nst | (uint32_t)odd << 16);
        uint32_t e1 = ht < nl ? lds32(sb + OFF_L + ht * 4) : 0u, e2 = ht + 128 < nl ? lds32(sb + OFF_L + (ht + 128) * 4) : 0u;
        load_row(w, e1);
        bar_sync(2, 128);
        if (lane == 0) mbar_arrive(sb + OFF_BAR + BAR_STAGE * 8); TS(19);
#pragma unroll 1
        for (int n = ht; n - lane < nl; n += 128) {
            const uint32_t e0 = e1;
            row_slots(w, v0, e0, plain, o);
            e1 = e2; load_row(w, e1);
            e2 = n + 256 < nl ? lds32(sb + OFF_L + (n + 256) * 4) : 0u;
            mbar_wait(sb + OFF_BAR + BAR_GRP * 8); TS((n < 128 ? 20 : 24 + min(n >> 7, 3)));
            if (n - lane + 31 >= nA) mbar_wait(sb + OFF_BAR + (BAR_GRP + 1) * 8);
            if (n < nl) lookup(o, sb, e0, tag, plain);
            __syncwarp();
        }
        TS(21);
#pragma unroll 1
        for (int n = (nAB > LCAP ? LCAP : nAB + nst) + ht; n - lane < nT; n += 128) {
            const uint32_t e0 = fetch_entry(n, nT, pre, base);
            mbar_wait(sb + OFF_BAR + (BAR_GRP + 2) * 8);
            if (n < nT) { load_row(w, e0); row_slots(w, v0, e0, plain, o); lookup(o, sb, e0, tag, plain); }
            __syncwarp();
        }
    }
    mbar_wait(sb + OFF_BAR + BAR_STAGE * 8);
    const uint2 ms = lds64(sb + OFF_MISC + 40);
    mbar_wait(sb + OFF_BAR + (BAR_GRP + 2) * 8);
    if (tid < (int)(ms.y & 0xffffu)) staged_lookup(sb, tid, ms.x, ms.y < 0x10000u);
    __syncwarp(); TS((tid >> 7) * 8 + 6);
    combine(out, ms.x); TS((tid >> 7) * 8 + 7);
}

}

extern "C" void kernel_launch(void* const* d_in, const int* in_sizes, int n_in, void* d_out, int out_size) {
    static bool configured = false;
    if (!configured) {
        cudaFuncSetAttribute(afm_kernel, cudaFuncAttributeMaxDynamicSharedMemorySize, SMEM_BYTES);
        configured = true;
    }
    afm_kernel<<<NCTA, NTHR, SMEM_BYTES>>>((const int*)d_in[0], (const uint8_t*)d_in[1], (const int*)d_in[2], (const int*)d_in[3],
                                           (const uint8_t*)d_in[4], (const uint8_t*)d_in[5], (const uint8_t*)d_in[6],
                                           (const uint8_t*)d_in[7], (__nv_bfloat16*)d_out);
}
```
